```python
import torch

def _softmax(x, axis=-1):
    return torch.softmax(x, dim=axis)
def _gelu(x):
    return torch.nn.functional.gelu(x, approximate="tanh")
def _silu(x):
    return torch.nn.functional.silu(x)
def _sigmoid(x):
    return torch.sigmoid(x)
def _layernorm(x, axis=-1, eps=1e-5):
    m = x.mean(dim=axis, keepdim=True)
    v = x.var(dim=axis, keepdim=True, unbiased=False)
    return (x - m) / torch.sqrt(v + eps)
def _scatter_add(tgt, idx, src, axis=0):
    return tgt.clone().index_add_(axis, idx, src)
def _segment_sum(src, seg, n):
    out = torch.zeros((n,) + src.shape[1:], dtype=src.dtype)
    return out.index_add_(0, seg, src)
def _pad(x, pw):
    flat = tuple(v for pair in reversed(pw) for v in pair)
    return torch.nn.functional.pad(x, flat)

kernel_name = 'recurrent_scan__ssm_conv_h3__glu_gated_bilinear__prompt'

def setup_inputs():

    _w = (lambda a: (lambda t: t.to(torch.bfloat16) if t.is_floating_point() else t)(torch.as_tensor(a)))
    def _A_setup():
        B, S, D = 1, 2048, 512
        ks = 4
        return {
            "q": _w((lambda *s: torch.randn(*s, dtype=torch.bfloat16) * 0.05)(B, S, D)),
            "k": _w((lambda *s: torch.randn(*s, dtype=torch.bfloat16) * 0.8)(B, S, D)),
            "v": _w((lambda *s: torch.randn(*s, dtype=torch.bfloat16) * 0.8)(B, S, D)),
            "shift_k": _w((lambda *s: torch.randn(*s, dtype=torch.bfloat16) * 0.8)(D, ks) * 0.5),
            "ssm_k": _w((lambda *s: torch.randn(*s, dtype=torch.bfloat16) * 0.8)(D, S) * (1.0 / S ** 0.5)),
            "ssm_D": _w((lambda *s: torch.randn(*s, dtype=torch.bfloat16) * 0.8)(D)),
        }
    _A_in = _A_setup()

    def _B_setup():
        B, S, D, F = 1, 2048, 512, 1376
        return {
            "x": _w((lambda *s: torch.randn(*s, dtype=torch.bfloat16) * 0.05)(B, S, D)),
            "w_gate": _w((lambda *s: torch.randn(*s, dtype=torch.bfloat16) * 0.2)(D, F) * (D ** -0.5)),
            "w_up": _w((lambda *s: torch.randn(*s, dtype=torch.bfloat16) * 0.2)(D, F) * (D ** -0.5)),
            "w_down": _w((lambda *s: torch.randn(*s, dtype=torch.bfloat16) * 0.2)(F, D) * (F ** -0.5)),
        }
    _B_in = _B_setup()

    return {
        "A_q": _A_in["q"],
        "A_k": _A_in["k"],
        "A_v": _A_in["v"],
        "A_shift_k": _A_in["shift_k"],
        "A_ssm_k": _A_in["ssm_k"],
        "A_ssm_D": _A_in["ssm_D"],
        "B_x": _B_in["x"],
        "B_w_gate": _B_in["w_gate"],
        "B_w_up": _B_in["w_up"],
        "B_w_down": _B_in["w_down"],
    }

def reference(A_q, A_k, A_v, A_shift_k, A_ssm_k, A_ssm_D, B_x, B_w_gate, B_w_up, B_w_down):
    def _A_ref(q, k, v, shift_k, ssm_k, ssm_D):
        B, S, D = q.shape
        ks = shift_k.shape[-1]
        k_pad = _pad(k, ((0, 0), (ks - 1, 0), (0, 0)))
        k_shift = torch.zeros_like(k)
        for t in range(ks):
            k_shift = k_shift + k_pad[:, t:t + S, :] * shift_k[:, ks - 1 - t][None, None, :]
        kv = k_shift * v
        L = 2 * S
        kv_pad = _pad(kv, ((0, 0), (0, S), (0, 0)))
        kf_pad = _pad(ssm_k, ((0, 0), (0, S)))
        kv_f = (lambda x, axes=(-2,-1): torch.fft.rfft2(x.float(), dim=axes))(kv_pad[:, None, :, :], axes=(1, 2))
        kf_f = (lambda x, axes=(-2,-1): torch.fft.rfft2(x.float(), dim=axes))(kf_pad[:, None, :], axes=(1, 2))
        kf_f = (lambda x, *d: x.permute(*d))(kf_f, 1, 2, 0)
        y_f = kv_f * kf_f[None, :, :, :]
        y = (lambda x, s, axes=(-2,-1): torch.fft.irfft2(x, s=s, dim=axes).to(torch.bfloat16))(y_f, (1, L), axes=(1, 2))[:, 0, :S, :]
        y = y + kv * ssm_D[None, None, :]
        return q * y

    def _B_ref(x, w_gate, w_up, w_down):
        g = torch.einsum("bsd,df->bsf", x, w_gate)
        u = torch.einsum("bsd,df->bsf", x, w_up)
        h = g * u
        return torch.einsum("bsf,fd->bsd", h, w_down)

    x = A_q
    xn = _layernorm(x, axis=-1)
    s = _A_ref(xn, A_k, A_v, A_shift_k, A_ssm_k, A_ssm_D)
    g = _silu(_B_ref(xn, B_w_gate, B_w_up, B_w_down))
    return x + s * g
```

```cpp
#include <cuda_runtime.h>
#include <cuda_bf16.h>
#include <cuda.h>
#include <stdint.h>

#define HAVE_SCRATCH 1

namespace {

constexpr int S_LEN = 2048, D_DIM = 512, F_DIM = 1376;
constexpr int NCTA = 128, NTHREADS = 384;
constexpr int NST = 5;
constexpr int WST = 24576, XST = 16384, STAGE = 32768;
constexpr int G1_STAGES = 16, G2_STAGES = 12;
constexpr int FCH = 176;
constexpr int UR_A = 4224;
constexpr int UR_CH = 2 * UR_A;
constexpr int G_CH = 4352;
constexpr int KV_STAGE = 132 * 128;
constexpr int OFF_X = NST * WST;
constexpr int OFF_UR = OFF_X + 3 * XST;
constexpr int OFF_G = OFF_UR + 4 * UR_CH;
constexpr int OFF_CS = OFF_G + 4 * G_CH;
constexpr int OFF_ST = OFF_CS + 1536;
constexpr int OFF_BAR = OFF_ST + 1024;
constexpr int SMEM_BYTES = OFF_BAR + 512 + 1024;
constexpr int BAR_FW = 0, BAR_EW = 40, BAR_F2 = 80, BAR_E2 = 120, BAR_FX = 160, BAR_EX = 184;
constexpr int BAR_CONVK = 208, BAR_PEER = 216, BAR_XCH = 224, BAR_KV = 232, BAR_G1 = 240, BAR_STG = 248, BAR_GO = 256;
constexpr unsigned SPIN_LIMIT = 1u << 22;

#define JCL jc
#define M1L m1
#define G2_RHO0 5
#define G2_MID 5
#define KV_IT 1
#define MAPMODE 1
#define MAP_SLOT(c) ((((c) & 7) << 3) | ((c) >> 3))

}

__device__ __nv_bfloat16 g_h[S_LEN * F_DIM];
__device__ __nv_bfloat16 g_yt[D_DIM * S_LEN];
__device__ uint4 g_ura[16 * D_DIM * 16];
__device__ uint4 g_urb[16 * D_DIM * 16];
__device__ float g_cspart[8 * 16 * 2 * FCH];
__device__ unsigned g_cscnt[8];
__device__ float2 g_stats[S_LEN];
__device__ unsigned g_stcnt[16];
__device__ unsigned g_hcnt[16 * 8 * 2];
__device__ unsigned g_kvcnt[8];
__device__ unsigned g_ycnt[8];
__device__ unsigned g_done;
__device__ unsigned g_epoch;
#define TRACE(i) do { } while (0)

namespace {

__device__ __forceinline__ long long globaltimer_ns() { long long t; asm volatile("mov.u64 %0, %%clock64;" : "=l"(t)); return t; }
__device__ __forceinline__ long long gtime() { long long t; asm volatile("mov.u64 %0, %%globaltimer;" : "=l"(t)); return t; }
__device__ __forceinline__ uint32_t smem_u32(const void* p) { return (uint32_t)__cvta_generic_to_shared(p); }

__device__ __forceinline__ void mbar_init(uint32_t b, uint32_t c) { asm volatile("mbarrier.init.shared::cta.b64 [%0], %1;" ::"r"(b), "r"(c) : "memory"); }
__device__ __forceinline__ void mbar_expect_tx(uint32_t b, uint32_t bytes) { asm volatile("mbarrier.arrive.expect_tx.shared::cta.b64 _, [%0], %1;" ::"r"(b), "r"(bytes) : "memory"); }
__device__ __forceinline__ void mbar_arrive(uint32_t b) { asm volatile("mbarrier.arrive.shared::cta.b64 _, [%0];" ::"r"(b) : "memory"); }
__device__ __forceinline__ void mbar_arrive_cnt(uint32_t b, uint32_t c) { asm volatile("mbarrier.arrive.shared::cta.b64 _, [%0], %1;" ::"r"(b), "r"(c) : "memory"); }
__device__ __forceinline__ void mbar_arrive_remote(uint32_t remote) { asm volatile("mbarrier.arrive.shared::cluster.b64 _, [%0];" ::"r"(remote) : "memory"); }
__device__ __forceinline__ void mbar_wait(uint32_t b, uint32_t parity) {
  uint32_t ok;
  unsigned spins = 0;
  do {
    asm volatile("{\n.reg .pred p;\nmbarrier.try_wait.parity.shared::cta.b64 p, [%1], %2;\nselp.u32 %0, 1, 0, p;\n}" : "=r"(ok) : "r"(b), "r"(parity) : "memory");
  } while (!ok && ++spins < SPIN_LIMIT);
}
__device__ __forceinline__ bool mbar_test(uint32_t b, uint32_t parity) {
  uint32_t ok;
  asm volatile("{\n.reg .pred p;\nmbarrier.test_wait.parity.shared::cta.b64 p, [%1], %2;\nselp.u32 %0, 1, 0, p;\n}" : "=r"(ok) : "r"(b), "r"(parity) : "memory");
  return ok != 0;
}
__device__ __forceinline__ void mbar_wait_cluster(uint32_t b, uint32_t parity) {
  uint32_t ok;
  unsigned spins = 0;
  do {
    asm volatile("{\n.reg .pred p;\nmbarrier.try_wait.parity.acquire.cluster.shared::cta.b64 p, [%1], %2;\nselp.u32 %0, 1, 0, p;\n}" : "=r"(ok) : "r"(b), "r"(parity) : "memory");
  } while (!ok && ++spins < SPIN_LIMIT);
}
__device__ __forceinline__ uint32_t mapa(uint32_t addr, uint32_t rank) { uint32_t r; asm volatile("mapa.shared::cluster.u32 %0, %1, %2;" : "=r"(r) : "r"(addr), "r"(rank)); return r; }
__device__ __forceinline__ void tma_load_2d(uint32_t dst, const CUtensorMap* m, int c0, int c1, uint32_t mbar) {
  asm volatile("cp.async.bulk.tensor.2d.shared::cluster.global.mbarrier::complete_tx::bytes [%0], [%1, {%3, %4}], [%2];"
               ::"r"(dst), "l"(m), "r"(mbar), "r"(c0), "r"(c1) : "memory");
}
__device__ __forceinline__ void tma_load_3d(uint32_t dst, const CUtensorMap* m, int c0, int c1, int c2, uint32_t mbar) {
  asm volatile("cp.async.bulk.tensor.3d.shared::cluster.global.mbarrier::complete_tx::bytes [%0], [%1, {%3, %4, %5}], [%2];"
               ::"r"(dst), "l"(m), "r"(mbar), "r"(c0), "r"(c1), "r"(c2) : "memory");
}
__device__ __forceinline__ void tma_load_2d_mc(uint32_t dst, const CUtensorMap* m, int c0, int c1, uint32_t mbar) {
  asm volatile("cp.async.bulk.tensor.2d.shared::cluster.global.mbarrier::complete_tx::bytes.multicast::cluster [%0], [%1, {%3, %4}], [%2], %5;"
               ::"r"(dst), "l"(m), "r"(mbar), "r"(c0), "r"(c1), "h"((unsigned short)3) : "memory");
}
__device__ __forceinline__ void tma_prefetch_2d(const CUtensorMap* m, int c0, int c1) {
  asm volatile("cp.async.bulk.prefetch.tensor.2d.L2.global [%0, {%1, %2}];" ::"l"(m), "r"(c0), "r"(c1) : "memory");
}
__device__ __forceinline__ void tma_store_2d(const CUtensorMap* m, uint32_t src, int c0, int c1) {
  asm volatile("cp.async.bulk.tensor.2d.global.shared::cta.bulk_group [%0, {%2, %3}], [%1];" ::"l"(m), "r"(src), "r"(c0), "r"(c1) : "memory");
}
__device__ __forceinline__ void bulk_load(uint32_t dst, const void* src, uint32_t bytes, uint32_t mbar) {
  asm volatile("cp.async.bulk.shared::cluster.global.mbarrier::complete_tx::bytes [%0], [%1], %2, [%3];" ::"r"(dst), "l"(src), "r"(bytes), "r"(mbar) : "memory");
}
__device__ __forceinline__ void bulk_prefetch_l2(const void* src, uint32_t bytes) {
  asm volatile("cp.async.bulk.prefetch.L2.global [%0], %1;" ::"l"(src), "r"(bytes) : "memory");
}
__device__ __forceinline__ uint2 lds64(uint32_t addr) { uint2 v; asm volatile("ld.shared.v2.u32 {%0,%1}, [%2];" : "=r"(v.x), "=r"(v.y) : "r"(addr) : "memory"); return v; }
__device__ __forceinline__ void prefetch_tmap(const CUtensorMap* m) { asm volatile("prefetch.tensormap [%0];" ::"l"(m) : "memory"); }
__device__ __forceinline__ void fence_proxy_async() { asm volatile("fence.proxy.async.global;" ::: "memory"); }
__device__ __forceinline__ void fence_proxy_async_smem() { asm volatile("fence.proxy.async.shared::cta;" ::: "memory"); }
template <int ID, int N> __device__ __forceinline__ void bar_sync() { asm volatile("bar.sync %0, %1;" ::"n"(ID), "n"(N) : "memory"); }
template <int ID, int N> __device__ __forceinline__ void bar_arrive() { asm volatile("bar.arrive %0, %1;" ::"n"(ID), "n"(N) : "memory"); }
__device__ __forceinline__ void cluster_arrive() { asm volatile("barrier.cluster.arrive.relaxed.aligned;" ::: "memory"); }
__device__ __forceinline__ void cluster_wait() { asm volatile("barrier.cluster.wait.acquire.aligned;" ::: "memory"); }
__device__ __forceinline__ unsigned ld_acquire(const unsigned* p) { unsigned v; asm volatile("ld.acquire.gpu.global.u32 %0, [%1];" : "=r"(v) : "l"(p) : "memory"); return v; }
__device__ __forceinline__ void red_release(unsigned* p, unsigned v) { asm volatile("red.release.gpu.global.add.u32 [%0], %1;" ::"l"(p), "r"(v) : "memory"); }
__device__ __forceinline__ void red_relaxed(unsigned* p, unsigned v) { asm volatile("red.relaxed.gpu.global.add.u32 [%0], %1;" ::"l"(p), "r"(v) : "memory"); }
__device__ __forceinline__ void wait_counter(const unsigned* p, unsigned target) {
  unsigned spins = 0;
  while ((int)(ld_acquire(p) - target) < 0 && ++spins < SPIN_LIMIT) { __nanosleep(32); }
}
__device__ __forceinline__ void wg_fence() { asm volatile("wgmma.fence.sync.aligned;" ::: "memory"); }
__device__ __forceinline__ void wg_commit() { asm volatile("wgmma.commit_group.sync.aligned;" ::: "memory"); }
template <int N> __device__ __forceinline__ void wg_wait() { asm volatile("wgmma.wait_group.sync.aligned %0;" ::"n"(N) : "memory"); }
__device__ __forceinline__ uint64_t make_desc(uint32_t saddr, uint32_t lbo, uint32_t sbo) {
  return (uint64_t)((saddr & 0x3FFFF) >> 4) | ((uint64_t)(lbo >> 4) << 16) | ((uint64_t)(sbo >> 4) << 32) | (1ull << 62);
}
__device__ __forceinline__ void ldsm_x4(uint32_t addr, uint32_t& r0, uint32_t& r1, uint32_t& r2, uint32_t& r3) {
  asm volatile("ldmatrix.sync.aligned.m8n8.x4.shared.b16 {%0,%1,%2,%3}, [%4];" : "=r"(r0), "=r"(r1), "=r"(r2), "=r"(r3) : "r"(addr) : "memory");
}
__device__ __forceinline__ void ldsm_x4_t(uint32_t addr, uint32_t& r0, uint32_t& r1, uint32_t& r2, uint32_t& r3) {
  asm volatile("ldmatrix.sync.aligned.m8n8.x4.trans.shared.b16 {%0,%1,%2,%3}, [%4];" : "=r"(r0), "=r"(r1), "=r"(r2), "=r"(r3) : "r"(addr) : "memory");
}
__device__ __forceinline__ void stsm_x4(uint32_t addr, uint32_t r0, uint32_t r1, uint32_t r2, uint32_t r3) {
  asm volatile("stmatrix.sync.aligned.m8n8.x4.shared.b16 [%0], {%1,%2,%3,%4};" ::"r"(addr), "r"(r0), "r"(r1), "r"(r2), "r"(r3) : "memory");
}
__device__ __forceinline__ uint32_t lds32(uint32_t addr) { uint32_t v; asm volatile("ld.shared.u32 %0, [%1];" : "=r"(v) : "r"(addr) : "memory"); return v; }
__device__ __forceinline__ float2 lds64f(uint32_t addr) { float2 v; asm volatile("ld.shared.v2.f32 {%0,%1}, [%2];" : "=f"(v.x), "=f"(v.y) : "r"(addr) : "memory"); return v; }
__device__ __forceinline__ void sts32f(uint32_t addr, float v) { asm volatile("st.shared.f32 [%0], %1;" ::"r"(addr), "f"(v) : "memory"); }
__device__ __forceinline__ uint4 lds128(uint32_t addr) { uint4 v; asm volatile("ld.shared.v4.u32 {%0,%1,%2,%3}, [%4];" : "=r"(v.x), "=r"(v.y), "=r"(v.z), "=r"(v.w) : "r"(addr) : "memory"); return v; }
__device__ __forceinline__ float tanh_fast(float x) { float r; asm("tanh.approx.f32 %0, %1;" : "=f"(r) : "f"(x)); return r; }
__device__ __forceinline__ float4 lds128f(uint32_t addr) { float4 v; asm volatile("ld.shared.v4.f32 {%0,%1,%2,%3}, [%4];" : "=f"(v.x), "=f"(v.y), "=f"(v.z), "=f"(v.w) : "r"(addr) : "memory"); return v; }
__device__ __forceinline__ void sts128(uint32_t addr, uint32_t a, uint32_t b, uint32_t c, uint32_t d) {
  asm volatile("st.shared.v4.u32 [%0], {%1,%2,%3,%4};" ::"r"(addr), "r"(a), "r"(b), "r"(c), "r"(d) : "memory");
}
__device__ __forceinline__ void st_async_v4(uint32_t remote, float a, float b, float c, float d, uint32_t remote_bar) {
  asm volatile("st.async.shared::cluster.mbarrier::complete_tx::bytes.v4.f32 [%0], {%1,%2,%3,%4}, [%5];"
               ::"r"(remote), "f"(a), "f"(b), "f"(c), "f"(d), "r"(remote_bar) : "memory");
}
__device__ __forceinline__ void mma16816(float (&c)[4], uint32_t a0, uint32_t a1, uint32_t a2, uint32_t a3, uint32_t b0, uint32_t b1) {
  asm volatile("mma.sync.aligned.m16n8k16.row.col.f32.bf16.bf16.f32 {%0,%1,%2,%3}, {%4,%5,%6,%7}, {%8,%9}, {%0,%1,%2,%3};"
               : "+f"(c[0]), "+f"(c[1]), "+f"(c[2]), "+f"(c[3]) : "r"(a0), "r"(a1), "r"(a2), "r"(a3), "r"(b0), "r"(b1));
}
__device__ __forceinline__ uint32_t bsub2(uint32_t a, uint32_t b) { uint32_t r; asm("sub.rn.bf16x2 %0, %1, %2;" : "=r"(r) : "r"(a), "r"(b)); return r; }
__device__ __forceinline__ uint32_t badd2(uint32_t a, uint32_t b) { uint32_t r; asm("add.rn.bf16x2 %0, %1, %2;" : "=r"(r) : "r"(a), "r"(b)); return r; }
__device__ __forceinline__ uint32_t bmul2(uint32_t a, uint32_t b) { uint32_t r; asm("mul.rn.bf16x2 %0, %1, %2;" : "=r"(r) : "r"(a), "r"(b)); return r; }
__device__ __forceinline__ uint32_t pack_bf16(float lo, float hi) { uint32_t r; asm("cvt.rn.bf16x2.f32 %0, %1, %2;" : "=r"(r) : "f"(hi), "f"(lo)); return r; }
__device__ __forceinline__ float bf_lo(uint32_t v) { return __uint_as_float(v << 16); }
__device__ __forceinline__ float bf_hi(uint32_t v) { return __uint_as_float(v & 0xffff0000u); }
__device__ __forceinline__ float round_bf16(float f) { return bf_lo(pack_bf16(f, 0.f)); }
__device__ __forceinline__ uint4 ldg_nc(const uint4* p) {
  uint4 v; asm volatile("ld.global.nc.L1::no_allocate.v4.u32 {%0,%1,%2,%3}, [%4];" : "=r"(v.x), "=r"(v.y), "=r"(v.z), "=r"(v.w) : "l"(p)); return v;
}
__device__ __forceinline__ uint2 ldg_nc2(const void* p) {
  uint2 v; asm volatile("ld.global.nc.v2.u32 {%0,%1}, [%2];" : "=r"(v.x), "=r"(v.y) : "l"(p)); return v;
}

__device__ __forceinline__ void wgmma_ss_n176(float (&d)[88], uint64_t da, uint64_t db) {
  asm volatile("wgmma.mma_async.sync.aligned.m64n176k16.f32.bf16.bf16 "
    "{%0,%1,%2,%3,%4,%5,%6,%7,%8,%9,%10,%11,%12,%13,%14,%15,%16,%17,%18,%19,%20,%21,%22,%23,%24,%25,%26,%27,%28,%29,%30,%31,%32,%33,%34,%35,%36,%37,%38,%39,%40,%41,%42,%43,%44,%45,%46,%47,%48,%49,%50,%51,%52,%53,%54,%55,%56,%57,%58,%59,%60,%61,%62,%63,%64,%65,%66,%67,%68,%69,%70,%71,%72,%73,%74,%75,%76,%77,%78,%79,%80,%81,%82,%83,%84,%85,%86,%87}, "
    "%88, %89, 1, 1, 1, 0, 1;"
    : "+f"(d[0]), "+f"(d[1]), "+f"(d[2]), "+f"(d[3]), "+f"(d[4]), "+f"(d[5]), "+f"(d[6]), "+f"(d[7]),
      "+f"(d[8]), "+f"(d[9]), "+f"(d[10]), "+f"(d[11]), "+f"(d[12]), "+f"(d[13]), "+f"(d[14]), "+f"(d[15]),
      "+f"(d[16]), "+f"(d[17]), "+f"(d[18]), "+f"(d[19]), "+f"(d[20]), "+f"(d[21]), "+f"(d[22]), "+f"(d[23]),
      "+f"(d[24]), "+f"(d[25]), "+f"(d[26]), "+f"(d[27]), "+f"(d[28]), "+f"(d[29]), "+f"(d[30]), "+f"(d[31]),
      "+f"(d[32]), "+f"(d[33]), "+f"(d[34]), "+f"(d[35]), "+f"(d[36]), "+f"(d[37]), "+f"(d[38]), "+f"(d[39]),
      "+f"(d[40]), "+f"(d[41]), "+f"(d[42]), "+f"(d[43]), "+f"(d[44]), "+f"(d[45]), "+f"(d[46]), "+f"(d[47]),
      "+f"(d[48]), "+f"(d[49]), "+f"(d[50]), "+f"(d[51]), "+f"(d[52]), "+f"(d[53]), "+f"(d[54]), "+f"(d[55]),
      "+f"(d[56]), "+f"(d[57]), "+f"(d[58]), "+f"(d[59]), "+f"(d[60]), "+f"(d[61]), "+f"(d[62]), "+f"(d[63]),
      "+f"(d[64]), "+f"(d[65]), "+f"(d[66]), "+f"(d[67]), "+f"(d[68]), "+f"(d[69]), "+f"(d[70]), "+f"(d[71]),
      "+f"(d[72]), "+f"(d[73]), "+f"(d[74]), "+f"(d[75]), "+f"(d[76]), "+f"(d[77]), "+f"(d[78]), "+f"(d[79]),
      "+f"(d[80]), "+f"(d[81]), "+f"(d[82]), "+f"(d[83]), "+f"(d[84]), "+f"(d[85]), "+f"(d[86]), "+f"(d[87])
    : "l"(da), "l"(db));
}

__device__ __forceinline__ void wgmma_ss_n184(float (&d)[92], uint64_t da, uint64_t db) {
  asm volatile("wgmma.mma_async.sync.aligned.m64n184k16.f32.bf16.bf16 "
    "{%0,%1,%2,%3,%4,%5,%6,%7,%8,%9,%10,%11,%12,%13,%14,%15,%16,%17,%18,%19,%20,%21,%22,%23,%24,%25,%26,%27,%28,%29,%30,%31,%32,%33,%34,%35,%36,%37,%38,%39,%40,%41,%42,%43,%44,%45,%46,%47,%48,%49,%50,%51,%52,%53,%54,%55,%56,%57,%58,%59,%60,%61,%62,%63,%64,%65,%66,%67,%68,%69,%70,%71,%72,%73,%74,%75,%76,%77,%78,%79,%80,%81,%82,%83,%84,%85,%86,%87,%88,%89,%90,%91}, "
    "%92, %93, 1, 1, 1, 0, 1;"
    : "+f"(d[0]), "+f"(d[1]), "+f"(d[2]), "+f"(d[3]), "+f"(d[4]), "+f"(d[5]), "+f"(d[6]), "+f"(d[7]),
      "+f"(d[8]), "+f"(d[9]), "+f"(d[10]), "+f"(d[11]), "+f"(d[12]), "+f"(d[13]), "+f"(d[14]), "+f"(d[15]),
      "+f"(d[16]), "+f"(d[17]), "+f"(d[18]), "+f"(d[19]), "+f"(d[20]), "+f"(d[21]), "+f"(d[22]), "+f"(d[23]),
      "+f"(d[24]), "+f"(d[25]), "+f"(d[26]), "+f"(d[27]), "+f"(d[28]), "+f"(d[29]), "+f"(d[30]), "+f"(d[31]),
      "+f"(d[32]), "+f"(d[33]), "+f"(d[34]), "+f"(d[35]), "+f"(d[36]), "+f"(d[37]), "+f"(d[38]), "+f"(d[39]),
      "+f"(d[40]), "+f"(d[41]), "+f"(d[42]), "+f"(d[43]), "+f"(d[44]), "+f"(d[45]), "+f"(d[46]), "+f"(d[47]),
      "+f"(d[48]), "+f"(d[49]), "+f"(d[50]), "+f"(d[51]), "+f"(d[52]), "+f"(d[53]), "+f"(d[54]), "+f"(d[55]),
      "+f"(d[56]), "+f"(d[57]), "+f"(d[58]), "+f"(d[59]), "+f"(d[60]), "+f"(d[61]), "+f"(d[62]), "+f"(d[63]),
      "+f"(d[64]), "+f"(d[65]), "+f"(d[66]), "+f"(d[67]), "+f"(d[68]), "+f"(d[69]), "+f"(d[70]), "+f"(d[71]),
      "+f"(d[72]), "+f"(d[73]), "+f"(d[74]), "+f"(d[75]), "+f"(d[76]), "+f"(d[77]), "+f"(d[78]), "+f"(d[79]),
      "+f"(d[80]), "+f"(d[81]), "+f"(d[82]), "+f"(d[83]), "+f"(d[84]), "+f"(d[85]), "+f"(d[86]), "+f"(d[87]),
      "+f"(d[88]), "+f"(d[89]), "+f"(d[90]), "+f"(d[91])
    : "l"(da), "l"(db));
}

__device__ __forceinline__ void wgmma_ss_n128(float (&d)[64], uint64_t da, uint64_t db) {
  asm volatile("wgmma.mma_async.sync.aligned.m64n128k16.f32.bf16.bf16 "
    "{%0,%1,%2,%3,%4,%5,%6,%7,%8,%9,%10,%11,%12,%13,%14,%15,%16,%17,%18,%19,%20,%21,%22,%23,%24,%25,%26,%27,%28,%29,%30,%31,%32,%33,%34,%35,%36,%37,%38,%39,%40,%41,%42,%43,%44,%45,%46,%47,%48,%49,%50,%51,%52,%53,%54,%55,%56,%57,%58,%59,%60,%61,%62,%63}, "
    "%64, %65, 1, 1, 1, 0, 1;"
    : "+f"(d[0]), "+f"(d[1]), "+f"(d[2]), "+f"(d[3]), "+f"(d[4]), "+f"(d[5]), "+f"(d[6]), "+f"(d[7]),
      "+f"(d[8]), "+f"(d[9]), "+f"(d[10]), "+f"(d[11]), "+f"(d[12]), "+f"(d[13]), "+f"(d[14]), "+f"(d[15]),
      "+f"(d[16]), "+f"(d[17]), "+f"(d[18]), "+f"(d[19]), "+f"(d[20]), "+f"(d[21]), "+f"(d[22]), "+f"(d[23]),
      "+f"(d[24]), "+f"(d[25]), "+f"(d[26]), "+f"(d[27]), "+f"(d[28]), "+f"(d[29]), "+f"(d[30]), "+f"(d[31]),
      "+f"(d[32]), "+f"(d[33]), "+f"(d[34]), "+f"(d[35]), "+f"(d[36]), "+f"(d[37]), "+f"(d[38]), "+f"(d[39]),
      "+f"(d[40]), "+f"(d[41]), "+f"(d[42]), "+f"(d[43]), "+f"(d[44]), "+f"(d[45]), "+f"(d[46]), "+f"(d[47]),
      "+f"(d[48]), "+f"(d[49]), "+f"(d[50]), "+f"(d[51]), "+f"(d[52]), "+f"(d[53]), "+f"(d[54]), "+f"(d[55]),
      "+f"(d[56]), "+f"(d[57]), "+f"(d[58]), "+f"(d[59]), "+f"(d[60]), "+f"(d[61]), "+f"(d[62]), "+f"(d[63])
    : "l"(da), "l"(db));
}

template <int PART>
__device__ __forceinline__ void conv_rho(float (&acc)[11][4], uint32_t gaddr, uint32_t f0, uint32_t f1) {
  constexpr int T0 = PART ? 11 : 0, T1 = PART ? 16 : 11;
  uint32_t F[T1][2];
#pragma unroll
  for (int b = 0; b < T1; b++) {
    F[b][0] = lds32(f0 - 256 * b);
    F[b][1] = lds32(f1 - 256 * b);
  }
#pragma unroll
  for (int a = 0; a < T1; a++) {
    uint32_t a0, a1, a2, a3;
    ldsm_x4(gaddr + 256 * a, a0, a1, a2, a3);
#pragma unroll
    for (int i = T0; i < T1; i++)
      if (i >= a) mma16816(acc[i - T0], a0, a1, a2, a3, F[i - a][0], F[i - a][1]);
  }
}
template <int PART>
__device__ __forceinline__ void conv_store(float (&acc)[11][4], uint32_t kvaddr, uint32_t dd, __nv_bfloat16* yrow) {
  constexpr int T0 = PART ? 11 : 0, T1 = PART ? 16 : 11;
#pragma unroll
  for (int i = T0; i < T1; i++) {
#pragma unroll
    for (int hh = 0; hh < 2; hh++) {
      uint32_t w = lds32(kvaddr - 256 * i - 128 * hh);
      w = __byte_perm(w, w, 0x1032);
      uint32_t y = pack_bf16(acc[i - T0][2 * hh], acc[i - T0][2 * hh + 1]);
      y = badd2(y, bmul2(w, dd));
      *reinterpret_cast<uint32_t*>(yrow + 128 * i + 64 * hh) = y;
    }
  }
}

}

__global__ void __cluster_dims__(2, 1, 1) __launch_bounds__(NTHREADS, 1)
h3_glu_kernel(const __grid_constant__ CUtensorMap tm_x, const __grid_constant__ CUtensorMap tm_out,
              const __grid_constant__ CUtensorMap tm_wg, const __grid_constant__ CUtensorMap tm_wu,
              const __grid_constant__ CUtensorMap tm_wg48, const __grid_constant__ CUtensorMap tm_wu48,
              const __grid_constant__ CUtensorMap tm_wd, const __grid_constant__ CUtensorMap tm_hld,
              const __grid_constant__ CUtensorMap tm_wd48, const __grid_constant__ CUtensorMap tm_hld48,
              const __grid_constant__ CUtensorMap tm_hst64, const __grid_constant__ CUtensorMap tm_hst48,
              const __grid_constant__ CUtensorMap tm_yt, const __grid_constant__ CUtensorMap tm_k, const __grid_constant__ CUtensorMap tm_v,
              const __grid_constant__ CUtensorMap tm_ura, const __grid_constant__ CUtensorMap tm_urb,
              const __nv_bfloat16* __restrict__ x, const __nv_bfloat16* __restrict__ wgate, const __nv_bfloat16* __restrict__ wup,
              const __nv_bfloat16* __restrict__ shift_k, const __nv_bfloat16* __restrict__ ssm_k, const __nv_bfloat16* __restrict__ ssm_D) {
  extern __shared__ unsigned char smem_raw[];
  const uint32_t sb = (smem_u32(smem_raw) + 1023u) & ~1023u;
  const uint32_t bars = sb + OFF_BAR;
  const int tid = threadIdx.x, wid = tid >> 5, lane = tid & 31;
  const int bid = blockIdx.x;
  const int cl = bid >> 1, rank = bid & 1;
  const int sl = MAP_SLOT(cl);
  const int grp8 = sl >> 3, in8 = sl & 7;
  const int m1 = 2 * (4 * (grp8 >> 2) + (in8 >> 1)) + rank;
  const int jc = 2 * (grp8 & 3) + (in8 & 1);
  const int m2 = 2 * grp8 + (in8 >> 2);
  const int nt = in8 & 3;
  const int kh = rank;
  const int kbase = kh * 4 * FCH;
  const int ocol = 128 * nt + 64 * kh;

  if (tid == 0) {
    for (int i = 0; i < NST; i++) {
      mbar_init(bars + BAR_FW + 8 * i, 1); mbar_init(bars + BAR_EW + 8 * i, 4);
      mbar_init(bars + BAR_F2 + 8 * i, 1); mbar_init(bars + BAR_E2 + 8 * i, 2);
    }
    for (int i = 0; i < 3; i++) { mbar_init(bars + BAR_FX + 8 * i, 1); mbar_init(bars + BAR_EX + 8 * i, 2); }
    mbar_init(bars + BAR_CONVK, 1);
    mbar_init(bars + BAR_KV, 1);
    mbar_init(bars + BAR_PEER, 8);
    mbar_init(bars + BAR_XCH, 1);
    mbar_init(bars + BAR_G1, 2);
    mbar_init(bars + BAR_STG, 2);
    mbar_init(bars + BAR_GO, 1);
    mbar_expect_tx(bars + BAR_XCH, 32768);
    asm volatile("fence.mbarrier_init.release.cluster;" ::: "memory");
    fence_proxy_async_smem();
    mbar_expect_tx(bars + BAR_FX, XST);
    tma_load_2d(sb + OFF_X, &tm_x, 0, 128 * m1, bars + BAR_FX);
  }
  if (tid >= 32 && tid < 32 + NST * 32) {
    const int i = tid - 32, r = i & 31;
    sts128(sb + (i >> 5) * WST + 8192 + r * 128 + ((6 ^ (r & 7)) << 4), 0x3F803F80u, 0x3F803F80u, 0x3F803F80u, 0x3F803F80u);
    fence_proxy_async_smem();
  }
  __syncthreads();
  cluster_arrive();

  if (wid >= 8) {
    asm volatile("setmaxnreg.dec.sync.aligned.u32 88;");
    cluster_wait();
    if (wid == 8) {
      if (lane == 0) {
        const CUtensorMap* tw = rank ? &tm_wu : &tm_wg;
        const CUtensorMap* tw48 = rank ? &tm_wu48 : &tm_wg48;
        const uint32_t woff = rank ? 12288u : 0u;
        int slot = 0, it = 0, xb = 1, xs = 1;
        uint32_t par = 1, xpar = 1;
        unsigned spins = 0;
        while ((it < G1_STAGES || xb < G1_STAGES / 2) && ++spins < SPIN_LIMIT) {
          if (it < G1_STAGES && (it < NST || mbar_test(bars + BAR_EW + 8 * slot, par))) {
            const uint32_t st = sb + slot * WST, fb = bars + BAR_FW + 8 * slot;
            if (it == 8) TRACE(22);
            if (it == 12) TRACE(23);
            mbar_expect_tx(fb, 2 * 32 * FCH * 2);
            tma_load_2d_mc(st + woff, tw, FCH * jc, 32 * it, fb);
            tma_load_2d_mc(st + woff + 4096, tw, FCH * jc + 64, 32 * it, fb);
            tma_load_2d_mc(st + woff + 8192, tw48, FCH * jc + 128, 32 * it, fb);
            if (it == KV_IT) {
              mbar_expect_tx(bars + BAR_KV, 2 * KV_STAGE);
              tma_load_2d(sb + OFF_UR, &tm_k, 64 * (bid & 7), 128 * (bid >> 3) - 4, bars + BAR_KV);
              tma_load_2d(sb + OFF_UR + KV_STAGE, &tm_v, 64 * (bid & 7), 128 * (bid >> 3) - 4, bars + BAR_KV);
            }
            it++;
            if (++slot == NST) { slot = 0; par ^= 1; }
          }
          if (xb < G1_STAGES / 2 && 2 * xb <= it + 1 && (xb < 3 || mbar_test(bars + BAR_EX + 8 * xs, xpar))) {
            mbar_expect_tx(bars + BAR_FX + 8 * xs, XST);
            tma_load_2d(sb + OFF_X + xs * XST, &tm_x, 64 * xb, 128 * m1, bars + BAR_FX + 8 * xs);
            xb++;
            if (++xs == 3) { xs = 0; xpar ^= 1; }
          }
        }
        const unsigned epoch1 = *(volatile unsigned*)&g_epoch + 1u;
        slot = 0; par = 1;
        for (int s = 0; s <= G2_STAGES; s++) {
          const uint32_t st = sb + slot * STAGE, fb = bars + BAR_F2 + 8 * slot;
          if (s == 0) mbar_wait(bars + BAR_G1, 0);
          else if (s == 3) mbar_wait(bars + BAR_STG, 0);
          else if (s >= NST) mbar_wait(bars + BAR_E2 + 8 * slot, par);
          if (s < G2_STAGES) {
            const int c = s < 4 ? s : (s - 4) >> 1, sub = s < 4 ? 0 : 1 + ((s - 4) & 1);
            const int k0 = kbase + FCH * c + 64 * sub;
            const CUtensorMap* tb_ = sub < 2 ? &tm_wd : &tm_wd48;
            mbar_expect_tx(fb, sub < 2 ? STAGE : STAGE / 4 * 3);
            tma_load_2d(st + 16384, tb_, 128 * nt, k0, fb);
            tma_load_2d(st + 24576, tb_, 128 * nt + 64, k0, fb);
            if (sub < 2) {
              wait_counter(&g_hcnt[(m2 * 8 + 4 * kh + c) * 2 + sub], 2u * epoch1);
              fence_proxy_async();
            }
            tma_load_2d(st, sub < 2 ? &tm_hld : &tm_hld48, k0, 128 * m2, fb);
          } else {
            mbar_expect_tx(fb, STAGE + 1024);
            tma_load_2d(st, &tm_x, ocol, 128 * m2, fb);
            wait_counter(&g_stcnt[m2], 24u * epoch1);
            wait_counter(&g_ycnt[ocol >> 6], 16u * epoch1);
            fence_proxy_async();
            bulk_load(sb + OFF_ST, g_stats + 128 * m2, 1024, fb);
            tma_load_2d(st + 16384, &tm_yt, 128 * m2, ocol, fb);
            tma_load_2d(st + 24576, &tm_yt, 128 * m2 + 64, ocol, fb);
          }
          if (++slot == NST) { slot = 0; par ^= 1; }
        }
        unsigned old = atomicInc(&g_done, NCTA - 1);
        if (old == NCTA - 1) atomicAdd(&g_epoch, 1u);
      }
    } else {
      const int at = tid - 288;
      const unsigned epoch1 = *(volatile unsigned*)&g_epoch + 1u;
      if (at < 60) sts128(sb + OFF_G + (at / 15) * G_CH + (at % 15) * 16, 0, 0, 0, 0);
      const int tb = bid >> 3;
      const int chp = 64 * (bid & 7) + 2 * (lane >> 1);
      const uint4 swa = *reinterpret_cast<const uint4*>(shift_k + chp * 4), swb = *reinterpret_cast<const uint4*>(shift_k + (chp + 32) * 4);
      if (at < 88) {
        const int c4 = (at < 44 ? at : at - 44) * 4;
        const int col = FCH * jc + c4;
        float s0 = 0.f, s1 = 0.f, s2 = 0.f, s3 = 0.f;
        if (col < F_DIM) {
          const __nv_bfloat16* wp = (at < 44 ? wgate : wup) + (size_t)(32 * m1) * F_DIM + col;
          uint2 w[32];
#pragma unroll
          for (int r = 0; r < 32; r++) w[r] = ldg_nc2(wp + (size_t)r * F_DIM);
#pragma unroll
          for (int r = 0; r < 32; r++) { s0 += bf_lo(w[r].x); s1 += bf_hi(w[r].x); s2 += bf_lo(w[r].y); s3 += bf_hi(w[r].y); }
        }
        *reinterpret_cast<float4*>(g_cspart + (size_t)(jc * 16 + m1) * (2 * FCH) + at * 4) = make_float4(s0, s1, s2, s3);
      }
      TRACE(18);
      bar_sync<6, 96>();
      if (at == 64) red_release(&g_cscnt[jc], 1u);
      mbar_wait(bars + BAR_KV, 0);
      TRACE(11);
#pragma unroll 1
      for (int u = wid - 9; u < 8; u += 3) {
        const int c8 = 2 * u + (lane & 1);
        const uint32_t ka = sb + OFF_UR + c8 * 1024 + (lane >> 1) * 4;
        uint32_t kk[2][12], r[2][9];
#pragma unroll
        for (int hf = 0; hf < 2; hf++) {
#pragma unroll
          for (int i = 0; i < 12; i++) kk[hf][i] = lds32(ka + hf * 64 + i * 128);
#pragma unroll
          for (int i = 0; i < 9; i++) r[hf][i] = lds32(ka + hf * 64 + KV_STAGE + (i + 3) * 128);
        }
#pragma unroll
        for (int hf = 0; hf < 2; hf++) {
          const uint4 sw = hf ? swb : swa;
          const uint32_t w0 = __byte_perm(sw.x, sw.z, 0x5410), w1 = __byte_perm(sw.x, sw.z, 0x7632);
          const uint32_t w2 = __byte_perm(sw.y, sw.w, 0x5410), w3 = __byte_perm(sw.y, sw.w, 0x7632);
          uint32_t(&rr)[9] = r[hf];
#pragma unroll
          for (int i = 0; i < 9; i++) {
            uint32_t a = bmul2(kk[hf][i], w3);
            a = badd2(a, bmul2(kk[hf][i + 1], w2));
            a = badd2(a, bmul2(kk[hf][i + 2], w1));
            a = badd2(a, bmul2(kk[hf][i + 3], w0));
            rr[i] = bmul2(a, rr[i]);
          }
          const size_t base = (size_t)((15 - tb) * D_DIM + chp + 32 * hf) * 16;
          uint4* da = g_ura + base + (15 - c8);
          uint4* db = g_urb + base + ((15 - c8) ^ 4);
          da[0] = make_uint4(__byte_perm(rr[8], rr[7], 0x5410), __byte_perm(rr[6], rr[5], 0x5410), __byte_perm(rr[4], rr[3], 0x5410), __byte_perm(rr[2], rr[1], 0x5410));
          da[16] = make_uint4(__byte_perm(rr[8], rr[7], 0x7632), __byte_perm(rr[6], rr[5], 0x7632), __byte_perm(rr[4], rr[3], 0x7632), __byte_perm(rr[2], rr[1], 0x7632));
          db[0] = make_uint4(__byte_perm(rr[7], rr[6], 0x5410), __byte_perm(rr[5], rr[4], 0x5410), __byte_perm(rr[3], rr[2], 0x5410), __byte_perm(rr[1], rr[0], 0x5410));
          db[16] = make_uint4(__byte_perm(rr[7], rr[6], 0x7632), __byte_perm(rr[5], rr[4], 0x7632), __byte_perm(rr[3], rr[2], 0x7632), __byte_perm(rr[1], rr[0], 0x7632));
        }
      }
      TRACE(13);
      bar_sync<6, 96>();
      TRACE(16);
      if (wid == 11) {
        if (lane == 0) {
          asm volatile("fence.acq_rel.gpu;" ::: "memory");
          red_relaxed(&g_kvcnt[bid & 7], 1u);
          mbar_expect_tx(bars + BAR_CONVK, 12 * 4096);
          for (int c = 0; c < 4; c++) bulk_load(sb + OFF_G + c * G_CH + 240, ssm_k + (size_t)(4 * bid + c) * S_LEN, 4096, bars + BAR_CONVK);
          wait_counter(&g_kvcnt[bid >> 4], 16u * epoch1);
          fence_proxy_async();
          for (int c = 0; c < 4; c++) {
            tma_load_3d(sb + OFF_UR + c * UR_CH, &tm_ura, 0, 4 * bid + c, 0, bars + BAR_CONVK);
            tma_load_3d(sb + OFF_UR + c * UR_CH + UR_A, &tm_urb, 0, 4 * bid + c, 0, bars + BAR_CONVK);
          }
        }
        TRACE(17);
        __syncwarp();
      {
        const int rbase = 128 * m1 + 16 * jc;
        uint4 v[6][2];
#pragma unroll
        for (int i = 0; i < 6; i++) {
          const int r = min(wid - 9 + 3 * i, 15);
          const uint4* pa = reinterpret_cast<const uint4*>(x + (size_t)(rbase + r) * D_DIM) + lane;
          v[i][0] = ldg_nc(pa); v[i][1] = ldg_nc(pa + 32);
        }
        float s[6], q2[6], c0[6];
#pragma unroll
        for (int i = 0; i < 6; i++) c0[i] = __shfl_sync(~0u, bf_lo(v[i][0].x), 0);
#pragma unroll
        for (int i = 0; i < 6; i++) {
          float a = 0.f, b = 0.f, d;
#pragma unroll
          for (int h = 0; h < 2; h++) {
            d = bf_lo(v[i][h].x) - c0[i]; a += d; b = fmaf(d, d, b); d = bf_hi(v[i][h].x) - c0[i]; a += d; b = fmaf(d, d, b);
            d = bf_lo(v[i][h].y) - c0[i]; a += d; b = fmaf(d, d, b); d = bf_hi(v[i][h].y) - c0[i]; a += d; b = fmaf(d, d, b);
            d = bf_lo(v[i][h].z) - c0[i]; a += d; b = fmaf(d, d, b); d = bf_hi(v[i][h].z) - c0[i]; a += d; b = fmaf(d, d, b);
            d = bf_lo(v[i][h].w) - c0[i]; a += d; b = fmaf(d, d, b); d = bf_hi(v[i][h].w) - c0[i]; a += d; b = fmaf(d, d, b);
          }
          s[i] = a; q2[i] = b;
        }
#pragma unroll
        for (int o = 16; o; o >>= 1)
#pragma unroll
          for (int i = 0; i < 6; i++) { s[i] += __shfl_xor_sync(~0u, s[i], o); q2[i] += __shfl_xor_sync(~0u, q2[i], o); }
        if (lane < 6) {
          float sm = s[0], qq = q2[0], cc = c0[0];
#pragma unroll
          for (int i = 1; i < 6; i++) if (lane == i) { sm = s[i]; qq = q2[i]; cc = c0[i]; }
          const float dm = sm * (1.f / D_DIM);
          const float var = fmaxf(fmaf(-dm, dm, qq * (1.f / D_DIM)), 0.f);
          const float sd = round_bf16(sqrtf(round_bf16(round_bf16(var) + 1e-5f)));
          g_stats[rbase + min(wid - 9 + 3 * lane, 15)] = make_float2(round_bf16(cc + dm), 1.f / sd);
        }
      }
        __syncwarp();
        if (lane == 0) red_release(&g_stcnt[m1], 1u);
        bar_sync<5, 288>();
        if (lane == 0) red_release(&g_ycnt[bid >> 4], 1u);
      } else {
        sts128(sb + OFF_UR + (at >> 3) * UR_A + 4096 + (at & 7) * 16, 0, 0, 0, 0);
        if (lane == 0) wait_counter(&g_cscnt[jc], 16u * epoch1);
        __syncwarp();
        TRACE(19);
        for (int c = at; c < 88; c += 64) {
          float4 s = make_float4(0.f, 0.f, 0.f, 0.f);
          const float4* cp = reinterpret_cast<const float4*>(g_cspart + (size_t)(jc * 16) * (2 * FCH)) + c;
#pragma unroll
          for (int mm = 0; mm < 16; mm++) {
            const float4 t = __ldcg(cp + mm * (2 * FCH / 4));
            s.x += t.x; s.y += t.y; s.z += t.z; s.w += t.w;
          }
          sts128(sb + OFF_CS + 16 * c, __float_as_uint(s.x), __float_as_uint(s.y), __float_as_uint(s.z), __float_as_uint(s.w));
        }
        TRACE(14);
        bar_arrive<4, 320>();
        const int g = wid - 9;
        const uint32_t st = sb + OFF_X + g * WST;
        if (g == 0) bar_sync<2, 160>(); else bar_sync<3, 160>();
        if (lane == 0) {
          tma_store_2d(&tm_hst64, st, FCH * jc, 128 * m1 + 64 * g);
          asm volatile("cp.async.bulk.commit_group;" ::: "memory");
        }
        __syncwarp();
        if (g == 0) bar_sync<7, 160>(); else bar_sync<8, 160>();
        if (lane == 0) {
          tma_store_2d(&tm_hst64, st + 8192, FCH * jc + 64, 128 * m1 + 64 * g);
          tma_store_2d(&tm_hst48, st + 16384, FCH * jc + 128, 128 * m1 + 64 * g);
          asm volatile("cp.async.bulk.commit_group;" ::: "memory");
          asm volatile("cp.async.bulk.wait_group 1;" ::: "memory");
          red_release(&g_hcnt[(m1 * 8 + jc) * 2], 1u);
          TRACE(24);
          asm volatile("cp.async.bulk.wait_group.read 0;" ::: "memory");
          mbar_arrive(bars + BAR_STG);
          asm volatile("cp.async.bulk.wait_group 0;" ::: "memory");
          red_release(&g_hcnt[(m1 * 8 + jc) * 2 + 1], 1u);
        }
        TRACE(15);
        __syncwarp();
      {
        const int rbase = 128 * m1 + 16 * jc;
        uint4 v[6][2];
#pragma unroll
        for (int i = 0; i < 6; i++) {
          const int r = min(wid - 9 + 3 * i, 15);
          const uint4* pa = reinterpret_cast<const uint4*>(x + (size_t)(rbase + r) * D_DIM) + lane;
          v[i][0] = ldg_nc(pa); v[i][1] = ldg_nc(pa + 32);
        }
        float s[6], q2[6], c0[6];
#pragma unroll
        for (int i = 0; i < 6; i++) c0[i] = __shfl_sync(~0u, bf_lo(v[i][0].x), 0);
#pragma unroll
        for (int i = 0; i < 6; i++) {
          float a = 0.f, b = 0.f, d;
#pragma unroll
          for (int h = 0; h < 2; h++) {
            d = bf_lo(v[i][h].x) - c0[i]; a += d; b = fmaf(d, d, b); d = bf_hi(v[i][h].x) - c0[i]; a += d; b = fmaf(d, d, b);
            d = bf_lo(v[i][h].y) - c0[i]; a += d; b = fmaf(d, d, b); d = bf_hi(v[i][h].y) - c0[i]; a += d; b = fmaf(d, d, b);
            d = bf_lo(v[i][h].z) - c0[i]; a += d; b = fmaf(d, d, b); d = bf_hi(v[i][h].z) - c0[i]; a += d; b = fmaf(d, d, b);
            d = bf_lo(v[i][h].w) - c0[i]; a += d; b = fmaf(d, d, b); d = bf_hi(v[i][h].w) - c0[i]; a += d; b = fmaf(d, d, b);
          }
          s[i] = a; q2[i] = b;
        }
#pragma unroll
        for (int o = 16; o; o >>= 1)
#pragma unroll
          for (int i = 0; i < 6; i++) { s[i] += __shfl_xor_sync(~0u, s[i], o); q2[i] += __shfl_xor_sync(~0u, q2[i], o); }
        if (lane < 6) {
          float sm = s[0], qq = q2[0], cc = c0[0];
#pragma unroll
          for (int i = 1; i < 6; i++) if (lane == i) { sm = s[i]; qq = q2[i]; cc = c0[i]; }
          const float dm = sm * (1.f / D_DIM);
          const float var = fmaxf(fmaf(-dm, dm, qq * (1.f / D_DIM)), 0.f);
          const float sd = round_bf16(sqrtf(round_bf16(round_bf16(var) + 1e-5f)));
          g_stats[rbase + min(wid - 9 + 3 * lane, 15)] = make_float2(round_bf16(cc + dm), 1.f / sd);
        }
      }
        __syncwarp();
        if (lane == 0) red_release(&g_stcnt[m1], 1u);
      }
    }
  } else {
    asm volatile("setmaxnreg.inc.sync.aligned.u32 208;");
    const int g = wid >> 2, w4 = wid & 3, p = lane >> 2, q = lane & 3;
    const int row0 = 64 * g + 16 * w4 + p;
    TRACE(0);
    cluster_wait();
    {
      float accg[92], accu[88];
#pragma unroll
      for (int i = 0; i < 88; i++) { accg[i] = 0.f; accu[i] = 0.f; }
      accg[88] = accg[89] = accg[90] = accg[91] = 0.f;
      const uint32_t peer_ew = mapa(bars + BAR_EW, rank ^ 1);
      int slot = 0, pslot = 0, xs = 0;
      uint32_t par = 0, xpar = 0;
#pragma unroll 1
      for (int it = 0; it < G1_STAGES; it++) {
        const uint32_t st = sb + slot * WST;
        const uint32_t xa = sb + OFF_X + xs * XST + g * 8192 + (it & 1) * 64;
        if (!(it & 1)) mbar_wait(bars + BAR_FX + 8 * xs, xpar);
        mbar_wait(bars + BAR_FW + 8 * slot, par);
        if (it == 0) TRACE(1);
        wg_fence();
        wgmma_ss_n184(accg, make_desc(xa, 16, 1024), make_desc(st, 4096, 1024));
        wgmma_ss_n176(accu, make_desc(xa, 16, 1024), make_desc(st + 12288, 4096, 1024));
        wgmma_ss_n184(accg, make_desc(xa + 32, 16, 1024), make_desc(st + 2048, 4096, 1024));
        wgmma_ss_n176(accu, make_desc(xa + 32, 16, 1024), make_desc(st + 12288 + 2048, 4096, 1024));
        wg_commit();
        if (it > 0) {
          wg_wait<1>();
          if ((tid & 127) == 0) {
            if (it - 1 < G1_STAGES - NST) {
              mbar_arrive(bars + BAR_EW + 8 * pslot);
              mbar_arrive_remote(peer_ew + 8 * pslot);
            }
            if (!(it & 1)) mbar_arrive(bars + BAR_EX + 8 * (xs == 0 ? 2 : xs - 1));
          }
        }
        pslot = slot;
        if (++slot == NST) { slot = 0; par ^= 1; }
        if (it & 1) { if (++xs == 3) { xs = 0; xpar ^= 1; } }
      }
      wg_wait<0>();
#pragma unroll
      for (int i = 0; i < 88; i++) { asm volatile("" : "+f"(accg[i])::"memory"); asm volatile("" : "+f"(accu[i])::"memory"); }
      asm volatile("" : "+f"(accg[88]), "+f"(accg[89]), "+f"(accg[90]), "+f"(accg[91])::"memory");
      if ((tid & 127) == 0) mbar_arrive(bars + BAR_G1);
      TRACE(2);
      bar_sync<4, 320>();
      const uint32_t stg = sb + OFF_X + g * WST;
      const int srow = 16 * w4 + (lane & 7) + 8 * ((lane >> 3) & 1);
      const float nm0 = -round_bf16(accg[88] * (1.f / D_DIM)), nm1 = -round_bf16(accg[90] * (1.f / D_DIM));
#pragma unroll
      for (int i = 0; i < 11; i++) {
        uint32_t h[4];
#pragma unroll
        for (int b = 0; b < 2; b++) {
          const int r = 8 * i + 4 * b;
          const float2 cg = lds64f(sb + OFF_CS + 4 * (16 * i + 8 * b) + 8 * q);
          const float2 cu = lds64f(sb + OFF_CS + 4 * FCH + 4 * (16 * i + 8 * b) + 8 * q);
          h[2 * b] = bmul2(pack_bf16(fmaf(nm0, cg.x, accg[r]), fmaf(nm0, cg.y, accg[r + 1])),
                           pack_bf16(fmaf(nm0, cu.x, accu[r]), fmaf(nm0, cu.y, accu[r + 1])));
          h[2 * b + 1] = bmul2(pack_bf16(fmaf(nm1, cg.x, accg[r + 2]), fmaf(nm1, cg.y, accg[r + 3])),
                               pack_bf16(fmaf(nm1, cu.x, accu[r + 2]), fmaf(nm1, cu.y, accu[r + 3])));
        }
        const int blkc = 2 * i + (lane >> 4);
        uint32_t addr;
        if (i < 8) addr = stg + (i >> 2) * 8192 + srow * 128 + (((blkc & 7) ^ (srow & 7)) << 4);
        else addr = stg + 16384 + srow * 96 + ((blkc - 16) << 4);
        stsm_x4(addr, h[0], h[1], h[2], h[3]);
        if (i == 3) {
          fence_proxy_async_smem();
          if (g == 0) bar_arrive<2, 160>(); else bar_arrive<3, 160>();
        }
      }
      fence_proxy_async_smem();
      if (g == 0) bar_arrive<7, 160>(); else bar_arrive<8, 160>();
    }
    TRACE(3);
    float acc[64];
#pragma unroll
    for (int i = 0; i < 64; i++) acc[i] = 0.f;
    int slot = 0, s2 = 0;
    uint32_t par = 0;
    auto gemm2_stages = [&](int send) {
      int pslot = -1;
#pragma unroll 1
      for (; s2 < send; s2++) {
        const uint32_t st = sb + slot * STAGE;
        mbar_wait(bars + BAR_F2 + 8 * slot, par);
        if (s2 < 4 || !(s2 & 1)) {
          wg_fence();
#pragma unroll
          for (int kk = 0; kk < 4; kk++)
            wgmma_ss_n128(acc, make_desc(st + g * 8192 + kk * 32, 16, 1024), make_desc(st + 16384 + kk * 2048, 8192, 1024));
          wg_commit();
        } else {
          wg_fence();
#pragma unroll
          for (int kk = 0; kk < 3; kk++)
            wgmma_ss_n128(acc, make_desc(st + g * 8192 + kk * 32, 16, 1024), make_desc(st + 16384 + kk * 2048, 8192, 1024));
          wg_commit();
        }
        if (pslot >= 0) {
          wg_wait<1>();
          if ((tid & 127) == 0) mbar_arrive(bars + BAR_E2 + 8 * pslot);
        }
        pslot = slot;
        if (++slot == NST) { slot = 0; par ^= 1; }
      }
      wg_wait<0>();
      if ((tid & 127) == 0) mbar_arrive(bars + BAR_E2 + 8 * pslot);
    };
    {
      const int ch = wid >> 1;
      const uint32_t urb = sb + OFF_UR + ch * UR_CH;
      const uint32_t gaddr = sb + OFF_G + ch * G_CH + 16 * ((lane & 7) + 8 * ((lane >> 3) & 1) + (lane >> 4));
      const uint32_t faddr = (p & 1) ? urb + 2 * (1927 - p + 2 * q) : urb + UR_A + 2 * (1926 - p + 2 * q);
      const uint32_t fxor = (p & 1) ? 0u : 64u;
      float cacc[11][4];
#pragma unroll
      for (int i = 0; i < 11; i++) cacc[i][0] = cacc[i][1] = cacc[i][2] = cacc[i][3] = 0.f;
      mbar_wait(bars + BAR_CONVK, 0);
      TRACE(4);
#pragma unroll 1
      for (int rho = 0; rho < 8; rho++) {
        if (rho == G2_RHO0) gemm2_stages(G2_MID);
        const uint32_t f0 = (faddr + 32 * rho) ^ fxor, f1 = (faddr + 32 * rho + 16) ^ fxor;
        if (wid & 1) conv_rho<1>(cacc, gaddr + 32 * rho, f0, f1);
        else conv_rho<0>(cacc, gaddr + 32 * rho, f0, f1);
      }
      const uint32_t kvaddr = urb + 2 * (2046 - 8 * p - 2 * q);
      const unsigned short dv = reinterpret_cast<const unsigned short*>(ssm_D)[4 * bid + ch];
      const uint32_t dd = (uint32_t)dv * 0x10001u;
      __nv_bfloat16* yrow = g_yt + (size_t)(4 * bid + ch) * S_LEN + 8 * p + 2 * q;
      if (wid & 1) conv_store<1>(cacc, kvaddr, dd, yrow);
      else conv_store<0>(cacc, kvaddr, dd, yrow);
      bar_arrive<5, 288>();
      if (lane == 0) mbar_arrive_remote(mapa(bars + BAR_PEER, rank ^ 1));
    }
    TRACE(5);
    gemm2_stages(G2_STAGES);
    mbar_wait(bars + BAR_PEER, 0);
#pragma unroll
    for (int i = 0; i < 64; i++) asm volatile("" : "+f"(acc[i])::"memory");
    TRACE(7);
    float o[32];
    {
      const uint32_t rbuf = mapa(sb + OFF_UR + tid * 16, rank ^ 1), rbar = mapa(bars + BAR_XCH, rank ^ 1);
      if (kh == 0) {
#pragma unroll
        for (int v = 0; v < 8; v++) st_async_v4(rbuf + v * 4096, acc[32 + 4 * v], acc[33 + 4 * v], acc[34 + 4 * v], acc[35 + 4 * v], rbar);
#pragma unroll
        for (int i = 0; i < 32; i++) o[i] = acc[i];
      } else {
#pragma unroll
        for (int v = 0; v < 8; v++) st_async_v4(rbuf + v * 4096, acc[4 * v], acc[1 + 4 * v], acc[2 + 4 * v], acc[3 + 4 * v], rbar);
#pragma unroll
        for (int i = 0; i < 32; i++) o[i] = acc[32 + i];
      }
    }
    {
      const uint32_t st = sb + slot * STAGE;
      mbar_wait(bars + BAR_F2 + 8 * slot, par);
      TRACE(8);
      const float2 st0 = lds64f(sb + OFF_ST + 8 * row0), st1 = lds64f(sb + OFF_ST + 8 * row0 + 64);
      const uint32_t mean0 = pack_bf16(st0.x, st0.x), mean1 = pack_bf16(st1.x, st1.x);
      uint32_t xv[16], sv[16];
      const int dl = (lane & 7) + 8 * (lane >> 4), tc = 2 * w4 + ((lane >> 3) & 1);
      const int xrow = 64 * g + 16 * w4 + (lane & 7) + 8 * ((lane >> 3) & 1);
#pragma unroll
      for (int v2 = 0; v2 < 4; v2++) {
        uint32_t y[4];
        const int d = 16 * v2 + dl;
        ldsm_x4_t(st + 16384 + g * 8192 + d * 128 + ((tc ^ (d & 7)) << 4), y[0], y[1], y[2], y[3]);
        ldsm_x4(st + xrow * 128 + (((2 * v2 + (lane >> 4)) ^ (xrow & 7)) << 4), xv[4 * v2], xv[4 * v2 + 1], xv[4 * v2 + 2], xv[4 * v2 + 3]);
#pragma unroll
        for (int e = 0; e < 4; e++) {
          const uint32_t xc = bsub2(xv[4 * v2 + e], (e & 1) ? mean1 : mean0);
          const float rs = (e & 1) ? st1.y : st0.y;
          sv[4 * v2 + e] = bmul2(pack_bf16(bf_lo(xc) * rs, bf_hi(xc) * rs), y[e]);
        }
      }
      mbar_wait(bars + BAR_XCH, 0);
      TRACE(9);
#pragma unroll
      for (int v2 = 0; v2 < 4; v2++) {
        uint32_t res[4];
#pragma unroll
        for (int b = 0; b < 2; b++) {
          const int v = 2 * v2 + b;
          const float4 r = lds128f(sb + OFF_UR + tid * 16 + v * 4096);
#pragma unroll
          for (int hh = 0; hh < 2; hh++) {
            const float r2 = hh ? st1.y * st1.y : st0.y * st0.y;
            const uint32_t ob = pack_bf16((o[4 * v + 2 * hh] + (hh ? r.z : r.x)) * r2, (o[4 * v + 2 * hh + 1] + (hh ? r.w : r.y)) * r2);
            const float h0 = 0.5f * bf_lo(ob), h1 = 0.5f * bf_hi(ob);
            const uint32_t gs = pack_bf16(fmaf(h0, tanh_fast(h0), h0), fmaf(h1, tanh_fast(h1), h1));
            res[2 * b + hh] = badd2(xv[4 * v2 + 2 * b + hh], bmul2(sv[4 * v2 + 2 * b + hh], gs));
          }
        }
        stsm_x4(st + xrow * 128 + (((2 * v2 + (lane >> 4)) ^ (xrow & 7)) << 4), res[0], res[1], res[2], res[3]);
      }
      fence_proxy_async_smem();
      if (g == 0) bar_sync<2, 128>(); else bar_sync<3, 128>();
      if ((tid & 127) == 0) {
        tma_store_2d(&tm_out, st + g * 8192, ocol, 128 * m2 + 64 * g);
        asm volatile("cp.async.bulk.commit_group;" ::: "memory");
        asm volatile("cp.async.bulk.wait_group.read 0;" ::: "memory");
      }
    }
    TRACE(10);
  }
}

typedef CUresult (*EncodeTiledFn)(CUtensorMap*, CUtensorMapDataType, cuuint32_t, void*, const cuuint64_t*, const cuuint64_t*,
                                  const cuuint32_t*, const cuuint32_t*, CUtensorMapInterleave, CUtensorMapSwizzle,
                                  CUtensorMapL2promotion, CUtensorMapFloatOOBfill);

static void make_map(EncodeTiledFn enc, CUtensorMap* m, const void* ptr, uint64_t cols, uint64_t rows, uint32_t bcols, uint32_t brows,
                     CUtensorMapSwizzle swz) {
  cuuint64_t dims[2] = {cols, rows};
  cuuint64_t strides[1] = {cols * 2};
  cuuint32_t box[2] = {bcols, brows};
  cuuint32_t es[2] = {1, 1};
  enc(m, CU_TENSOR_MAP_DATA_TYPE_BFLOAT16, 2, const_cast<void*>(ptr), dims, strides, box, es, CU_TENSOR_MAP_INTERLEAVE_NONE, swz,
      CU_TENSOR_MAP_L2_PROMOTION_L2_128B, CU_TENSOR_MAP_FLOAT_OOB_FILL_NONE);
}

extern "C" void kernel_launch(void* const* d_in, const int* in_sizes, int n_in, void* d_out, int out_size) {
  (void)in_sizes; (void)n_in; (void)out_size;
  const __nv_bfloat16* x = (const __nv_bfloat16*)d_in[0];
  const __nv_bfloat16* k = (const __nv_bfloat16*)d_in[1];
  const __nv_bfloat16* v = (const __nv_bfloat16*)d_in[2];
  const __nv_bfloat16* shift_k = (const __nv_bfloat16*)d_in[3];
  const __nv_bfloat16* ssm_k = (const __nv_bfloat16*)d_in[4];
  const __nv_bfloat16* ssm_D = (const __nv_bfloat16*)d_in[5];
  const __nv_bfloat16* wg = (const __nv_bfloat16*)d_in[7];
  const __nv_bfloat16* wu = (const __nv_bfloat16*)d_in[8];
  const __nv_bfloat16* wd = (const __nv_bfloat16*)d_in[9];

  static EncodeTiledFn enc = nullptr;
  static void* ph = nullptr;
  static void* pyt = nullptr;
  static void* pura = nullptr;
  static void* purb = nullptr;
  if (!enc) {
    void* fn = nullptr;
    cudaDriverEntryPointQueryResult qr;
    cudaGetDriverEntryPoint("cuTensorMapEncodeTiled", &fn, cudaEnableDefault, &qr);
    enc = (EncodeTiledFn)fn;
    cudaGetSymbolAddress(&ph, g_h);
    cudaGetSymbolAddress(&pyt, g_yt);
    cudaGetSymbolAddress(&pura, g_ura);
    cudaGetSymbolAddress(&purb, g_urb);
    cudaFuncSetAttribute(h3_glu_kernel, cudaFuncAttributeMaxDynamicSharedMemorySize, SMEM_BYTES);
  }
  CUtensorMap tm_x, tm_out, tm_wg, tm_wu, tm_wg48, tm_wu48, tm_wd, tm_hld, tm_wd48, tm_hld48, tm_hst64, tm_hst48, tm_yt, tm_k, tm_v, tm_ura, tm_urb;
  make_map(enc, &tm_x, x, D_DIM, S_LEN, 64, 128, CU_TENSOR_MAP_SWIZZLE_128B);
  make_map(enc, &tm_out, d_out, D_DIM, S_LEN, 64, 64, CU_TENSOR_MAP_SWIZZLE_128B);
  make_map(enc, &tm_wg, wg, F_DIM, D_DIM, 64, 32, CU_TENSOR_MAP_SWIZZLE_128B);
  make_map(enc, &tm_wu, wu, F_DIM, D_DIM, 64, 32, CU_TENSOR_MAP_SWIZZLE_128B);
  make_map(enc, &tm_wg48, wg, F_DIM, D_DIM, 48, 32, CU_TENSOR_MAP_SWIZZLE_128B);
  make_map(enc, &tm_wu48, wu, F_DIM, D_DIM, 48, 32, CU_TENSOR_MAP_SWIZZLE_128B);
  make_map(enc, &tm_wd, wd, D_DIM, F_DIM, 64, 64, CU_TENSOR_MAP_SWIZZLE_128B);
  make_map(enc, &tm_hld, ph, F_DIM, S_LEN, 64, 128, CU_TENSOR_MAP_SWIZZLE_128B);
  make_map(enc, &tm_wd48, wd, D_DIM, F_DIM, 64, 48, CU_TENSOR_MAP_SWIZZLE_128B);
  make_map(enc, &tm_hld48, ph, F_DIM, S_LEN, 48, 128, CU_TENSOR_MAP_SWIZZLE_128B);
  make_map(enc, &tm_hst64, ph, F_DIM, S_LEN, 64, 64, CU_TENSOR_MAP_SWIZZLE_128B);
  make_map(enc, &tm_hst48, ph, F_DIM, S_LEN, 48, 64, CU_TENSOR_MAP_SWIZZLE_NONE);
  make_map(enc, &tm_yt, pyt, S_LEN, D_DIM, 64, 64, CU_TENSOR_MAP_SWIZZLE_128B);
  make_map(enc, &tm_k, k, D_DIM, S_LEN, 64, 132, CU_TENSOR_MAP_SWIZZLE_NONE);
  make_map(enc, &tm_v, v, D_DIM, S_LEN, 64, 132, CU_TENSOR_MAP_SWIZZLE_NONE);
  for (int c = 0; c < 2; c++) {
    cuuint64_t dims[3] = {128, D_DIM, 16};
    cuuint64_t strides[2] = {256, (cuuint64_t)D_DIM * 256};
    cuuint32_t box[3] = {128, 1, 16};
    cuuint32_t es[3] = {1, 1, 1};
    enc(c ? &tm_urb : &tm_ura, CU_TENSOR_MAP_DATA_TYPE_BFLOAT16, 3, c ? purb : pura, dims, strides, box, es, CU_TENSOR_MAP_INTERLEAVE_NONE,
        CU_TENSOR_MAP_SWIZZLE_NONE, CU_TENSOR_MAP_L2_PROMOTION_L2_128B, CU_TENSOR_MAP_FLOAT_OOB_FILL_NONE);
  }
  h3_glu_kernel<<<NCTA, NTHREADS, SMEM_BYTES, cudaStreamPerThread>>>(tm_x, tm_out, tm_wg, tm_wu, tm_wg48, tm_wu48, tm_wd, tm_hld, tm_wd48, tm_hld48, tm_hst64, tm_hst48, tm_yt, tm_k, tm_v, tm_ura, tm_urb,
                                                                    x, wg, wu, shift_k, ssm_k, ssm_D);
}
```

```cpp
#include <cuda_runtime.h>
#include <cuda_bf16.h>
#include <cuda.h>
#include <stdint.h>

namespace {

constexpr int S_LEN = 2048, D_DIM = 512, F_DIM = 1376;
constexpr int NCTA = 128, NTHREADS = 384;
constexpr int BK1 = 32, G1_DEPTH = 0;
constexpr int NST = 5;
constexpr int NW = 160 / BK1;
constexpr int WATOM = BK1 * 128;
constexpr int WST = 6 * WATOM, XST = 16384, STAGE = 32768, HSTG = 24576;
constexpr int G1_STAGES = 512 / BK1, G2_STAGES = 12;
constexpr int XPER = 64 / BK1;
constexpr int FCH = 176;
constexpr int UR_A = 4224;
constexpr int UR_CH = 2 * UR_A;
constexpr int G_CH = 4352;
constexpr int KV_STAGE = 132 * 128;
constexpr int OFF_X = NW * WST;
constexpr int OFF_UR = OFF_X + 3 * XST;
constexpr int OFF_G = OFF_UR + 4 * UR_CH;
constexpr int OFF_CS = OFF_G + 4 * G_CH;
constexpr int OFF_ST = OFF_CS + 6144;
constexpr int OFF_BAR = OFF_ST + 1024;
constexpr int SMEM_BYTES = OFF_BAR + 512 + 1024;
constexpr int BAR_FW = 0, BAR_EW = 40, BAR_F2 = 80, BAR_E2 = 120, BAR_FX = 160, BAR_EX = 184;
constexpr int BAR_CONVK = 208, BAR_PEER = 216, BAR_XCH = 224, BAR_KV = 232, BAR_G1 = 240, BAR_STG = 248;
static_assert(NW == 5, "barrier layout");
constexpr unsigned SPIN_LIMIT = 1u << 20;

constexpr int G2_RHO0 = 6, G2_MID = 5;
constexpr int KV_IT = 6, PF_WD = 8;

__device__ __forceinline__ int map_slot(int c) {
  if (c < 4) return 4 + c;
  const int t = c - 4;
  if (t < 32) return ((t & 7) << 3) | (t >> 3);
  const int u = t - 32;
  return ((1 + u % 7) << 3) | (4 + u / 7);
}

}

__device__ __align__(1024) __nv_bfloat16 g_h[S_LEN * F_DIM];
__device__ __align__(1024) __nv_bfloat16 g_yt[D_DIM * S_LEN];
__device__ __align__(1024) uint4 g_ura[16 * D_DIM * 16];
__device__ __align__(1024) uint4 g_urb[16 * D_DIM * 16];
__device__ __align__(128) float g_cspart[8 * 16 * 2 * FCH];
__device__ unsigned g_cscnt[8];
__device__ __align__(128) float2 g_stats[S_LEN];
__device__ unsigned g_stcnt;
__device__ unsigned g_hcnt[16 * 8 * 2];
__device__ unsigned g_kvcnt[8];
__device__ unsigned g_ycnt[8];
__device__ unsigned g_done;
__device__ unsigned g_epoch;

namespace {

__device__ __forceinline__ uint32_t smem_u32(const void* p) { return (uint32_t)__cvta_generic_to_shared(p); }

__device__ __forceinline__ void mbar_init(uint32_t b, uint32_t c) { asm volatile("mbarrier.init.shared::cta.b64 [%0], %1;" ::"r"(b), "r"(c) : "memory"); }
__device__ __forceinline__ void mbar_expect_tx(uint32_t b, uint32_t bytes) { asm volatile("mbarrier.arrive.expect_tx.shared::cta.b64 _, [%0], %1;" ::"r"(b), "r"(bytes) : "memory"); }
__device__ __forceinline__ void mbar_arrive(uint32_t b) { asm volatile("mbarrier.arrive.shared::cta.b64 _, [%0];" ::"r"(b) : "memory"); }
__device__ __forceinline__ void mbar_arrive_remote(uint32_t remote) { asm volatile("mbarrier.arrive.shared::cluster.b64 _, [%0];" ::"r"(remote) : "memory"); }
__device__ __forceinline__ void mbar_wait(uint32_t b, uint32_t parity) {
  uint32_t ok;
  unsigned spins = 0;
  do {
    asm volatile("{\n.reg .pred p;\nmbarrier.try_wait.parity.shared::cta.b64 p, [%1], %2;\nselp.u32 %0, 1, 0, p;\n}" : "=r"(ok) : "r"(b), "r"(parity) : "memory");
  } while (!ok && ++spins < SPIN_LIMIT);
}
__device__ __forceinline__ bool mbar_test(uint32_t b, uint32_t parity) {
  uint32_t ok;
  asm volatile("{\n.reg .pred p;\nmbarrier.test_wait.parity.shared::cta.b64 p, [%1], %2;\nselp.u32 %0, 1, 0, p;\n}" : "=r"(ok) : "r"(b), "r"(parity) : "memory");
  return ok != 0;
}
__device__ __forceinline__ uint32_t mapa(uint32_t addr, uint32_t rank) { uint32_t r; asm volatile("mapa.shared::cluster.u32 %0, %1, %2;" : "=r"(r) : "r"(addr), "r"(rank)); return r; }
__device__ __forceinline__ void tma_load_2d(uint32_t dst, const CUtensorMap* m, int c0, int c1, uint32_t mbar) {
  asm volatile("cp.async.bulk.tensor.2d.shared::cluster.global.mbarrier::complete_tx::bytes [%0], [%1, {%3, %4}], [%2];"
               ::"r"(dst), "l"(m), "r"(mbar), "r"(c0), "r"(c1) : "memory");
}
__device__ __forceinline__ void tma_load_3d(uint32_t dst, const CUtensorMap* m, int c0, int c1, int c2, uint32_t mbar) {
  asm volatile("cp.async.bulk.tensor.3d.shared::cluster.global.mbarrier::complete_tx::bytes [%0], [%1, {%3, %4, %5}], [%2];"
               ::"r"(dst), "l"(m), "r"(mbar), "r"(c0), "r"(c1), "r"(c2) : "memory");
}
__device__ __forceinline__ void tma_load_3d_mc(uint32_t dst, const CUtensorMap* m, int c0, int c1, int c2, uint32_t mbar) {
  asm volatile("cp.async.bulk.tensor.3d.shared::cluster.global.mbarrier::complete_tx::bytes.multicast::cluster [%0], [%1, {%3, %4, %5}], [%2], %6;"
               ::"r"(dst), "l"(m), "r"(mbar), "r"(c0), "r"(c1), "r"(c2), "h"((unsigned short)3) : "memory");
}
__device__ __forceinline__ void tma_load_2d_mc(uint32_t dst, const CUtensorMap* m, int c0, int c1, uint32_t mbar) {
  asm volatile("cp.async.bulk.tensor.2d.shared::cluster.global.mbarrier::complete_tx::bytes.multicast::cluster [%0], [%1, {%3, %4}], [%2], %5;"
               ::"r"(dst), "l"(m), "r"(mbar), "r"(c0), "r"(c1), "h"((unsigned short)3) : "memory");
}
__device__ __forceinline__ void tma_store_2d(const CUtensorMap* m, uint32_t src, int c0, int c1) {
  asm volatile("cp.async.bulk.tensor.2d.global.shared::cta.bulk_group [%0, {%2, %3}], [%1];" ::"l"(m), "r"(src), "r"(c0), "r"(c1) : "memory");
}
__device__ __forceinline__ void bulk_load(uint32_t dst, const void* src, uint32_t bytes, uint32_t mbar) {
  asm volatile("cp.async.bulk.shared::cluster.global.mbarrier::complete_tx::bytes [%0], [%1], %2, [%3];" ::"r"(dst), "l"(src), "r"(bytes), "r"(mbar) : "memory");
}
__device__ __forceinline__ void bulk_prefetch_l2(const void* src, uint32_t bytes) {
  asm volatile("cp.async.bulk.prefetch.L2.global [%0], %1;" ::"l"(src), "r"(bytes) : "memory");
}
__device__ __forceinline__ void fence_proxy_async() { asm volatile("fence.proxy.async.global;" ::: "memory"); }
__device__ __forceinline__ void fence_proxy_async_smem() { asm volatile("fence.proxy.async.shared::cta;" ::: "memory"); }
template <int ID, int N> __device__ __forceinline__ void bar_sync() { asm volatile("bar.sync %0, %1;" ::"n"(ID), "n"(N) : "memory"); }
template <int ID, int N> __device__ __forceinline__ void bar_arrive() { asm volatile("bar.arrive %0, %1;" ::"n"(ID), "n"(N) : "memory"); }
__device__ __forceinline__ void cluster_arrive() { asm volatile("barrier.cluster.arrive.relaxed.aligned;" ::: "memory"); }
__device__ __forceinline__ void cluster_wait() { asm volatile("barrier.cluster.wait.acquire.aligned;" ::: "memory"); }
__device__ __forceinline__ unsigned ld_acquire(const unsigned* p) { unsigned v; asm volatile("ld.acquire.gpu.global.u32 %0, [%1];" : "=r"(v) : "l"(p) : "memory"); return v; }
__device__ __forceinline__ void red_release(unsigned* p, unsigned v) { asm volatile("red.release.gpu.global.add.u32 [%0], %1;" ::"l"(p), "r"(v) : "memory"); }
__device__ __forceinline__ void red_relaxed(unsigned* p, unsigned v) { asm volatile("red.relaxed.gpu.global.add.u32 [%0], %1;" ::"l"(p), "r"(v) : "memory"); }
__device__ __forceinline__ void wait_counter(const unsigned* p, unsigned target) {
  unsigned spins = 0;
  while ((int)(ld_acquire(p) - target) < 0 && ++spins < SPIN_LIMIT) { __nanosleep(32); }
}
__device__ __forceinline__ void wg_fence() { asm volatile("wgmma.fence.sync.aligned;" ::: "memory"); }
__device__ __forceinline__ void wg_commit() { asm volatile("wgmma.commit_group.sync.aligned;" ::: "memory"); }
template <int N> __device__ __forceinline__ void wg_wait() { asm volatile("wgmma.wait_group.sync.aligned %0;" ::"n"(N) : "memory"); }
__device__ __forceinline__ uint64_t make_desc(uint32_t saddr, uint32_t lbo, uint32_t sbo) {
  return (uint64_t)((saddr & 0x3FFFF) >> 4) | ((uint64_t)(lbo >> 4) << 16) | ((uint64_t)(sbo >> 4) << 32) | (1ull << 62);
}
__device__ __forceinline__ void ldsm_x4(uint32_t addr, uint32_t& r0, uint32_t& r1, uint32_t& r2, uint32_t& r3) {
  asm volatile("ldmatrix.sync.aligned.m8n8.x4.shared.b16 {%0,%1,%2,%3}, [%4];" : "=r"(r0), "=r"(r1), "=r"(r2), "=r"(r3) : "r"(addr) : "memory");
}
__device__ __forceinline__ void ldsm_x4_t(uint32_t addr, uint32_t& r0, uint32_t& r1, uint32_t& r2, uint32_t& r3) {
  asm volatile("ldmatrix.sync.aligned.m8n8.x4.trans.shared.b16 {%0,%1,%2,%3}, [%4];" : "=r"(r0), "=r"(r1), "=r"(r2), "=r"(r3) : "r"(addr) : "memory");
}
__device__ __forceinline__ void stsm_x4(uint32_t addr, uint32_t r0, uint32_t r1, uint32_t r2, uint32_t r3) {
  asm volatile("stmatrix.sync.aligned.m8n8.x4.shared.b16 [%0], {%1,%2,%3,%4};" ::"r"(addr), "r"(r0), "r"(r1), "r"(r2), "r"(r3) : "memory");
}
__device__ __forceinline__ uint32_t lds32(uint32_t addr) { uint32_t v; asm volatile("ld.shared.u32 %0, [%1];" : "=r"(v) : "r"(addr) : "memory"); return v; }
__device__ __forceinline__ float2 lds64f(uint32_t addr) { float2 v; asm volatile("ld.shared.v2.f32 {%0,%1}, [%2];" : "=f"(v.x), "=f"(v.y) : "r"(addr) : "memory"); return v; }
__device__ __forceinline__ void sts64(uint32_t addr, uint32_t a, uint32_t b) { asm volatile("st.shared.v2.u32 [%0], {%1,%2};" ::"r"(addr), "r"(a), "r"(b) : "memory"); }
__device__ __forceinline__ float tanh_fast(float x) { float r; asm("tanh.approx.f32 %0, %1;" : "=f"(r) : "f"(x)); return r; }
__device__ __forceinline__ float4 lds128f(uint32_t addr) { float4 v; asm volatile("ld.shared.v4.f32 {%0,%1,%2,%3}, [%4];" : "=f"(v.x), "=f"(v.y), "=f"(v.z), "=f"(v.w) : "r"(addr) : "memory"); return v; }
__device__ __forceinline__ void sts128(uint32_t addr, uint32_t a, uint32_t b, uint32_t c, uint32_t d) {
  asm volatile("st.shared.v4.u32 [%0], {%1,%2,%3,%4};" ::"r"(addr), "r"(a), "r"(b), "r"(c), "r"(d) : "memory");
}
__device__ __forceinline__ void st_async_v4(uint32_t remote, float a, float b, float c, float d, uint32_t remote_bar) {
  asm volatile("st.async.shared::cluster.mbarrier::complete_tx::bytes.v4.f32 [%0], {%1,%2,%3,%4}, [%5];"
               ::"r"(remote), "f"(a), "f"(b), "f"(c), "f"(d), "r"(remote_bar) : "memory");
}
__device__ __forceinline__ void mma16816(float (&c)[4], uint32_t a0, uint32_t a1, uint32_t a2, uint32_t a3, uint32_t b0, uint32_t b1) {
  asm volatile("mma.sync.aligned.m16n8k16.row.col.f32.bf16.bf16.f32 {%0,%1,%2,%3}, {%4,%5,%6,%7}, {%8,%9}, {%0,%1,%2,%3};"
               : "+f"(c[0]), "+f"(c[1]), "+f"(c[2]), "+f"(c[3]) : "r"(a0), "r"(a1), "r"(a2), "r"(a3), "r"(b0), "r"(b1));
}
__device__ __forceinline__ uint32_t bsub2(uint32_t a, uint32_t b) { uint32_t r; asm("sub.rn.bf16x2 %0, %1, %2;" : "=r"(r) : "r"(a), "r"(b)); return r; }
__device__ __forceinline__ uint32_t badd2(uint32_t a, uint32_t b) { uint32_t r; asm("add.rn.bf16x2 %0, %1, %2;" : "=r"(r) : "r"(a), "r"(b)); return r; }
__device__ __forceinline__ uint32_t bmul2(uint32_t a, uint32_t b) { uint32_t r; asm("mul.rn.bf16x2 %0, %1, %2;" : "=r"(r) : "r"(a), "r"(b)); return r; }
__device__ __forceinline__ uint32_t pack_bf16(float lo, float hi) { uint32_t r; asm("cvt.rn.bf16x2.f32 %0, %1, %2;" : "=r"(r) : "f"(hi), "f"(lo)); return r; }
__device__ __forceinline__ float bf_lo(uint32_t v) { return __uint_as_float(v << 16); }
__device__ __forceinline__ float bf_hi(uint32_t v) { return __uint_as_float(v & 0xffff0000u); }
__device__ __forceinline__ float round_bf16(float f) { return bf_lo(pack_bf16(f, 0.f)); }
__device__ __forceinline__ uint4 ldg_nc(const uint4* p) {
  uint4 v; asm volatile("ld.global.nc.L1::no_allocate.v4.u32 {%0,%1,%2,%3}, [%4];" : "=r"(v.x), "=r"(v.y), "=r"(v.z), "=r"(v.w) : "l"(p)); return v;
}
__device__ __forceinline__ uint2 ldg_nc2(const void* p) {
  uint2 v; asm volatile("ld.global.nc.v2.u32 {%0,%1}, [%2];" : "=r"(v.x), "=r"(v.y) : "l"(p)); return v;
}

__device__ __forceinline__ void wgmma_ss_n176(float (&d)[88], uint64_t da, uint64_t db) {
  asm volatile("wgmma.mma_async.sync.aligned.m64n176k16.f32.bf16.bf16 "
    "{%0,%1,%2,%3,%4,%5,%6,%7,%8,%9,%10,%11,%12,%13,%14,%15,%16,%17,%18,%19,%20,%21,%22,%23,%24,%25,%26,%27,%28,%29,%30,%31,%32,%33,%34,%35,%36,%37,%38,%39,%40,%41,%42,%43,%44,%45,%46,%47,%48,%49,%50,%51,%52,%53,%54,%55,%56,%57,%58,%59,%60,%61,%62,%63,%64,%65,%66,%67,%68,%69,%70,%71,%72,%73,%74,%75,%76,%77,%78,%79,%80,%81,%82,%83,%84,%85,%86,%87}, "
    "%88, %89, 1, 1, 1, 0, 1;"
    : "+f"(d[0]), "+f"(d[1]), "+f"(d[2]), "+f"(d[3]), "+f"(d[4]), "+f"(d[5]), "+f"(d[6]), "+f"(d[7]),
      "+f"(d[8]), "+f"(d[9]), "+f"(d[10]), "+f"(d[11]), "+f"(d[12]), "+f"(d[13]), "+f"(d[14]), "+f"(d[15]),
      "+f"(d[16]), "+f"(d[17]), "+f"(d[18]), "+f"(d[19]), "+f"(d[20]), "+f"(d[21]), "+f"(d[22]), "+f"(d[23]),
      "+f"(d[24]), "+f"(d[25]), "+f"(d[26]), "+f"(d[27]), "+f"(d[28]), "+f"(d[29]), "+f"(d[30]), "+f"(d[31]),
      "+f"(d[32]), "+f"(d[33]), "+f"(d[34]), "+f"(d[35]), "+f"(d[36]), "+f"(d[37]), "+f"(d[38]), "+f"(d[39]),
      "+f"(d[40]), "+f"(d[41]), "+f"(d[42]), "+f"(d[43]), "+f"(d[44]), "+f"(d[45]), "+f"(d[46]), "+f"(d[47]),
      "+f"(d[48]), "+f"(d[49]), "+f"(d[50]), "+f"(d[51]), "+f"(d[52]), "+f"(d[53]), "+f"(d[54]), "+f"(d[55]),
      "+f"(d[56]), "+f"(d[57]), "+f"(d[58]), "+f"(d[59]), "+f"(d[60]), "+f"(d[61]), "+f"(d[62]), "+f"(d[63]),
      "+f"(d[64]), "+f"(d[65]), "+f"(d[66]), "+f"(d[67]), "+f"(d[68]), "+f"(d[69]), "+f"(d[70]), "+f"(d[71]),
      "+f"(d[72]), "+f"(d[73]), "+f"(d[74]), "+f"(d[75]), "+f"(d[76]), "+f"(d[77]), "+f"(d[78]), "+f"(d[79]),
      "+f"(d[80]), "+f"(d[81]), "+f"(d[82]), "+f"(d[83]), "+f"(d[84]), "+f"(d[85]), "+f"(d[86]), "+f"(d[87])
    : "l"(da), "l"(db));
}

__device__ __forceinline__ void wgmma_ss_n184(float (&d)[92], uint64_t da, uint64_t db) {
  asm volatile("wgmma.mma_async.sync.aligned.m64n184k16.f32.bf16.bf16 "
    "{%0,%1,%2,%3,%4,%5,%6,%7,%8,%9,%10,%11,%12,%13,%14,%15,%16,%17,%18,%19,%20,%21,%22,%23,%24,%25,%26,%27,%28,%29,%30,%31,%32,%33,%34,%35,%36,%37,%38,%39,%40,%41,%42,%43,%44,%45,%46,%47,%48,%49,%50,%51,%52,%53,%54,%55,%56,%57,%58,%59,%60,%61,%62,%63,%64,%65,%66,%67,%68,%69,%70,%71,%72,%73,%74,%75,%76,%77,%78,%79,%80,%81,%82,%83,%84,%85,%86,%87,%88,%89,%90,%91}, "
    "%92, %93, 1, 1, 1, 0, 1;"
    : "+f"(d[0]), "+f"(d[1]), "+f"(d[2]), "+f"(d[3]), "+f"(d[4]), "+f"(d[5]), "+f"(d[6]), "+f"(d[7]),
      "+f"(d[8]), "+f"(d[9]), "+f"(d[10]), "+f"(d[11]), "+f"(d[12]), "+f"(d[13]), "+f"(d[14]), "+f"(d[15]),
      "+f"(d[16]), "+f"(d[17]), "+f"(d[18]), "+f"(d[19]), "+f"(d[20]), "+f"(d[21]), "+f"(d[22]), "+f"(d[23]),
      "+f"(d[24]), "+f"(d[25]), "+f"(d[26]), "+f"(d[27]), "+f"(d[28]), "+f"(d[29]), "+f"(d[30]), "+f"(d[31]),
      "+f"(d[32]), "+f"(d[33]), "+f"(d[34]), "+f"(d[35]), "+f"(d[36]), "+f"(d[37]), "+f"(d[38]), "+f"(d[39]),
      "+f"(d[40]), "+f"(d[41]), "+f"(d[42]), "+f"(d[43]), "+f"(d[44]), "+f"(d[45]), "+f"(d[46]), "+f"(d[47]),
      "+f"(d[48]), "+f"(d[49]), "+f"(d[50]), "+f"(d[51]), "+f"(d[52]), "+f"(d[53]), "+f"(d[54]), "+f"(d[55]),
      "+f"(d[56]), "+f"(d[57]), "+f"(d[58]), "+f"(d[59]), "+f"(d[60]), "+f"(d[61]), "+f"(d[62]), "+f"(d[63]),
      "+f"(d[64]), "+f"(d[65]), "+f"(d[66]), "+f"(d[67]), "+f"(d[68]), "+f"(d[69]), "+f"(d[70]), "+f"(d[71]),
      "+f"(d[72]), "+f"(d[73]), "+f"(d[74]), "+f"(d[75]), "+f"(d[76]), "+f"(d[77]), "+f"(d[78]), "+f"(d[79]),
      "+f"(d[80]), "+f"(d[81]), "+f"(d[82]), "+f"(d[83]), "+f"(d[84]), "+f"(d[85]), "+f"(d[86]), "+f"(d[87]),
      "+f"(d[88]), "+f"(d[89]), "+f"(d[90]), "+f"(d[91])
    : "l"(da), "l"(db));
}

__device__ __forceinline__ void wgmma_ss_n128(float (&d)[64], uint64_t da, uint64_t db) {
  asm volatile("wgmma.mma_async.sync.aligned.m64n128k16.f32.bf16.bf16 "
    "{%0,%1,%2,%3,%4,%5,%6,%7,%8,%9,%10,%11,%12,%13,%14,%15,%16,%17,%18,%19,%20,%21,%22,%23,%24,%25,%26,%27,%28,%29,%30,%31,%32,%33,%34,%35,%36,%37,%38,%39,%40,%41,%42,%43,%44,%45,%46,%47,%48,%49,%50,%51,%52,%53,%54,%55,%56,%57,%58,%59,%60,%61,%62,%63}, "
    "%64, %65, 1, 1, 1, 0, 1;"
    : "+f"(d[0]), "+f"(d[1]), "+f"(d[2]), "+f"(d[3]), "+f"(d[4]), "+f"(d[5]), "+f"(d[6]), "+f"(d[7]),
      "+f"(d[8]), "+f"(d[9]), "+f"(d[10]), "+f"(d[11]), "+f"(d[12]), "+f"(d[13]), "+f"(d[14]), "+f"(d[15]),
      "+f"(d[16]), "+f"(d[17]), "+f"(d[18]), "+f"(d[19]), "+f"(d[20]), "+f"(d[21]), "+f"(d[22]), "+f"(d[23]),
      "+f"(d[24]), "+f"(d[25]), "+f"(d[26]), "+f"(d[27]), "+f"(d[28]), "+f"(d[29]), "+f"(d[30]), "+f"(d[31]),
      "+f"(d[32]), "+f"(d[33]), "+f"(d[34]), "+f"(d[35]), "+f"(d[36]), "+f"(d[37]), "+f"(d[38]), "+f"(d[39]),
      "+f"(d[40]), "+f"(d[41]), "+f"(d[42]), "+f"(d[43]), "+f"(d[44]), "+f"(d[45]), "+f"(d[46]), "+f"(d[47]),
      "+f"(d[48]), "+f"(d[49]), "+f"(d[50]), "+f"(d[51]), "+f"(d[52]), "+f"(d[53]), "+f"(d[54]), "+f"(d[55]),
      "+f"(d[56]), "+f"(d[57]), "+f"(d[58]), "+f"(d[59]), "+f"(d[60]), "+f"(d[61]), "+f"(d[62]), "+f"(d[63])
    : "l"(da), "l"(db));
}


template <int PART>
__device__ __forceinline__ void conv_rho(float (&acc)[11][4], uint32_t gaddr, uint32_t f0, uint32_t f1) {
  constexpr int T0 = PART ? 11 : 0, T1 = PART ? 16 : 11;
  uint32_t F[T1][2];
#pragma unroll
  for (int b = 0; b < T1; b++) {
    F[b][0] = lds32(f0 - 256 * b);
    F[b][1] = lds32(f1 - 256 * b);
  }
#pragma unroll
  for (int a = 0; a < T1; a++) {
    uint32_t a0, a1, a2, a3;
    ldsm_x4(gaddr + 256 * a, a0, a1, a2, a3);
#pragma unroll
    for (int i = T0; i < T1; i++)
      if (i >= a) mma16816(acc[i - T0], a0, a1, a2, a3, F[i - a][0], F[i - a][1]);
  }
}
template <int PART>
__device__ __forceinline__ void conv_store(float (&acc)[11][4], uint32_t kvaddr, uint32_t dd, __nv_bfloat16* yrow) {
  constexpr int T0 = PART ? 11 : 0, T1 = PART ? 16 : 11;
#pragma unroll
  for (int i = T0; i < T1; i++) {
#pragma unroll
    for (int hh = 0; hh < 2; hh++) {
      uint32_t w = lds32(kvaddr - 256 * i - 128 * hh);
      w = __byte_perm(w, w, 0x1032);
      uint32_t y = pack_bf16(acc[i - T0][2 * hh], acc[i - T0][2 * hh + 1]);
      y = badd2(y, bmul2(w, dd));
      *reinterpret_cast<uint32_t*>(yrow + 128 * i + 64 * hh) = y;
    }
  }
}

}

__global__ void __cluster_dims__(2, 1, 1) __launch_bounds__(NTHREADS, 1)
h3_glu_kernel(const __grid_constant__ CUtensorMap tm_x, const __grid_constant__ CUtensorMap tm_out,
              const __grid_constant__ CUtensorMap tm_wg, const __grid_constant__ CUtensorMap tm_wu,
              const __grid_constant__ CUtensorMap tm_wg48, const __grid_constant__ CUtensorMap tm_wu48,
              const __grid_constant__ CUtensorMap tm_wd, const __grid_constant__ CUtensorMap tm_hld,
              const __grid_constant__ CUtensorMap tm_wd48, const __grid_constant__ CUtensorMap tm_hld48,
              const __grid_constant__ CUtensorMap tm_hst64, const __grid_constant__ CUtensorMap tm_hst48,
              const __grid_constant__ CUtensorMap tm_yt, const __grid_constant__ CUtensorMap tm_k, const __grid_constant__ CUtensorMap tm_v,
              const __grid_constant__ CUtensorMap tm_ura, const __grid_constant__ CUtensorMap tm_urb,
              const __nv_bfloat16* __restrict__ x, const __nv_bfloat16* __restrict__ wgate, const __nv_bfloat16* __restrict__ wup, const __nv_bfloat16* __restrict__ wdown,
              const __nv_bfloat16* __restrict__ shift_k, const __nv_bfloat16* __restrict__ ssm_k, const __nv_bfloat16* __restrict__ ssm_D) {
  extern __shared__ unsigned char smem_raw[];
  const uint32_t sb = (smem_u32(smem_raw) + 1023u) & ~1023u;
  const uint32_t bars = sb + OFF_BAR;
  const int tid = threadIdx.x, wid = tid >> 5, lane = tid & 31;
  const int bid = blockIdx.x;
  if (__builtin_expect(bid >= NCTA, 0)) {
    const int hb = bid - NCTA;
#pragma unroll 1
    for (int r0 = 512 * hb + 8 * wid; r0 < 512 * hb + 512; r0 += 96) {
      uint4 v[8][2];
#pragma unroll
      for (int i = 0; i < 8; i++) {
        const uint4* pa = reinterpret_cast<const uint4*>(x + (size_t)min(r0 + i, S_LEN - 1) * D_DIM) + lane;
        v[i][0] = ldg_nc(pa); v[i][1] = ldg_nc(pa + 32);
      }
      float s[8], q2[8], c0[8];
#pragma unroll
      for (int i = 0; i < 8; i++) c0[i] = __shfl_sync(~0u, bf_lo(v[i][0].x), 0);
#pragma unroll
      for (int i = 0; i < 8; i++) {
        float a = 0.f, b = 0.f, d;
#pragma unroll
        for (int h = 0; h < 2; h++) {
          d = bf_lo(v[i][h].x) - c0[i]; a += d; b = fmaf(d, d, b); d = bf_hi(v[i][h].x) - c0[i]; a += d; b = fmaf(d, d, b);
          d = bf_lo(v[i][h].y) - c0[i]; a += d; b = fmaf(d, d, b); d = bf_hi(v[i][h].y) - c0[i]; a += d; b = fmaf(d, d, b);
          d = bf_lo(v[i][h].z) - c0[i]; a += d; b = fmaf(d, d, b); d = bf_hi(v[i][h].z) - c0[i]; a += d; b = fmaf(d, d, b);
          d = bf_lo(v[i][h].w) - c0[i]; a += d; b = fmaf(d, d, b); d = bf_hi(v[i][h].w) - c0[i]; a += d; b = fmaf(d, d, b);
        }
        s[i] = a; q2[i] = b;
      }
#pragma unroll
      for (int o = 16; o; o >>= 1)
#pragma unroll
        for (int i = 0; i < 8; i++) { s[i] += __shfl_xor_sync(~0u, s[i], o); q2[i] += __shfl_xor_sync(~0u, q2[i], o); }
      if (lane < 8 && r0 + lane < 512 * hb + 512) {
        float sm = s[0], qq = q2[0], cc = c0[0];
#pragma unroll
        for (int i = 1; i < 8; i++) if (lane == i) { sm = s[i]; qq = q2[i]; cc = c0[i]; }
        const float dm = sm * (1.f / D_DIM);
        const float var = fmaxf(fmaf(-dm, dm, qq * (1.f / D_DIM)), 0.f);
        const float sd = round_bf16(sqrtf(round_bf16(round_bf16(var) + 1e-5f)));
        g_stats[r0 + lane] = make_float2(round_bf16(cc + dm), 1.f / sd);
      }
    }
    __syncthreads();
    if (tid == 0) red_release(&g_stcnt, 1u);
    return;
  }

  const int cl = bid >> 1, rank = bid & 1;
  const int sl = map_slot(cl);
  const int grp8 = sl >> 3, in8 = sl & 7;
  const int m1 = 2 * grp8 + rank;
  const int jc = in8;
  const int m2 = 2 * grp8 + (in8 >> 2);
  const int nt = in8 & 3;
  const int kh = rank;
  const int kbase = kh * 4 * FCH;
  const int ocol = 128 * nt + 64 * kh;

  if (tid == 0) {
#pragma unroll
    for (int i = 0; i < 5; i++) { mbar_init(bars + BAR_FW + 8 * i, 1); mbar_init(bars + BAR_EW + 8 * i, 4); }
#pragma unroll
    for (int i = 0; i < 3; i++) { mbar_init(bars + BAR_FX + 8 * i, 1); mbar_init(bars + BAR_EX + 8 * i, 2); }
#pragma unroll
    for (int i = 0; i < NST; i++) { mbar_init(bars + BAR_F2 + 8 * i, 1); mbar_init(bars + BAR_E2 + 8 * i, 2); }
    mbar_init(bars + BAR_CONVK, 1);
    mbar_init(bars + BAR_KV, 1);
    mbar_init(bars + BAR_PEER, 8);
    mbar_init(bars + BAR_XCH, 1);
    mbar_init(bars + BAR_G1, 2);
    mbar_init(bars + BAR_STG, 2);
    mbar_expect_tx(bars + BAR_XCH, 32768);
    asm volatile("fence.mbarrier_init.release.cluster;" ::: "memory");
    fence_proxy_async_smem();
    mbar_expect_tx(bars + BAR_FX, XST);
    tma_load_2d(sb + OFF_X, &tm_x, 0, 128 * m1, bars + BAR_FX);
  }
  __syncthreads();
  cluster_arrive();

  if (__builtin_expect(wid >= 8, 1)) {
    asm volatile("setmaxnreg.dec.sync.aligned.u32 88;");
    cluster_wait();
    if (__builtin_expect(wid == 8, 1)) {
      if (__builtin_expect(lane == 0, 1)) {
        const CUtensorMap* tw = rank ? &tm_wu : &tm_wg;
        const CUtensorMap* tw48 = rank ? &tm_wu48 : &tm_wg48;
        const uint32_t woff = rank ? 3u * WATOM : 0u;
        int slot = 0, it = 0, xb = 1, xs = 1;
        uint32_t par = 1, xpar = 1;
        unsigned spins = 0;
        while ((it < G1_STAGES || xb < 8) && ++spins < SPIN_LIMIT) {
          if (it < G1_STAGES && (it < NW || mbar_test(bars + BAR_EW + 8 * slot, par))) {
            const uint32_t st = sb + slot * WST, fb = bars + BAR_FW + 8 * slot;
            mbar_expect_tx(fb, 2 * BK1 * FCH * 2);
            tma_load_3d_mc(st + woff, tw, FCH * jc, BK1 * it, 0, fb);
            tma_load_2d_mc(st + woff + 2 * WATOM, tw48, FCH * jc + 128, BK1 * it, fb);
            if (it == PF_WD) bulk_prefetch_l2(wdown + (size_t)bid * (F_DIM * D_DIM / NCTA), F_DIM * D_DIM / NCTA * 2);
            if (it == KV_IT) {
              mbar_expect_tx(bars + BAR_KV, 2 * KV_STAGE);
              tma_load_2d(sb + OFF_UR, &tm_k, 64 * (bid & 7), 128 * (bid >> 3) - 4, bars + BAR_KV);
              tma_load_2d(sb + OFF_UR + KV_STAGE, &tm_v, 64 * (bid & 7), 128 * (bid >> 3) - 4, bars + BAR_KV);
            }
            it++;
            if (++slot == NW) { slot = 0; par ^= 1; }
          }
          if (xb < 8 && XPER * xb <= it + 1 && (xb < 3 || mbar_test(bars + BAR_EX + 8 * xs, xpar))) {
            mbar_expect_tx(bars + BAR_FX + 8 * xs, XST);
            tma_load_2d(sb + OFF_X + xs * XST, &tm_x, 64 * xb, 128 * m1, bars + BAR_FX + 8 * xs);
            xb++;
            if (++xs == 3) { xs = 0; xpar ^= 1; }
          }
        }
        const unsigned epoch1 = *(volatile unsigned*)&g_epoch + 1u;
        auto g2_k0 = [&](int s) { return kbase + FCH * (s < 4 ? s : (s - 4) >> 1) + 64 * (s < 4 ? 0 : 1 + ((s - 4) & 1)); };
        auto g2_wd = [&](int s, uint32_t st, uint32_t fb) {
          const bool wide = s < 4 || !(s & 1);
          mbar_expect_tx(fb, wide ? STAGE : STAGE / 4 * 3);
          if (wide) {
            tma_load_3d(st + 16384, &tm_wd, 128 * nt, g2_k0(s), 0, fb);
          } else {
            tma_load_2d(st + 16384, &tm_wd48, 128 * nt, g2_k0(s), fb);
            tma_load_2d(st + 24576, &tm_wd48, 128 * nt + 64, g2_k0(s), fb);
          }
        };
        auto g2_flag = [&](int s) { return &g_hcnt[(m2 * 8 + 4 * kh + (s < 4 ? s : (s - 4) >> 1)) * 2 + (s < 4 ? 0 : 1)]; };
        mbar_wait(bars + BAR_G1, 0);
        {
          int nw = 0, nh = 0;
          unsigned sp = 0;
          while (nh < NST && ++sp < SPIN_LIMIT) {
            if (nw < NST && (nw < 3 || mbar_test(bars + BAR_STG, 0))) {
              g2_wd(nw, sb + nw * STAGE, bars + BAR_F2 + 8 * nw);
              nw++;
            } else if (nh < nw && (int)(ld_acquire(g2_flag(nh)) - 2u * epoch1) >= 0) {
              fence_proxy_async();
              tma_load_2d(sb + nh * STAGE, &tm_hld, g2_k0(nh), 128 * m2, bars + BAR_F2 + 8 * nh);
              nh++;
            }
          }
        }
        slot = 0; par = 0;
        for (int s = NST; s <= G2_STAGES; s++) {
          const uint32_t st = sb + slot * STAGE, fb = bars + BAR_F2 + 8 * slot;
          mbar_wait(bars + BAR_E2 + 8 * slot, par);
          if (s < G2_STAGES) {
            const bool wide = !(s & 1);
            g2_wd(s, st, fb);
            if (wide) {
              wait_counter(g2_flag(s), 2u * epoch1);
              fence_proxy_async();
            }
            tma_load_2d(st, wide ? &tm_hld : &tm_hld48, g2_k0(s), 128 * m2, fb);
          } else {
            mbar_expect_tx(fb, STAGE + 1024);
            tma_load_2d(st, &tm_x, ocol, 128 * m2, fb);
            wait_counter(&g_stcnt, 4u * epoch1);
            wait_counter(&g_ycnt[ocol >> 6], 16u * epoch1);
            fence_proxy_async();
            bulk_load(sb + OFF_ST, g_stats + 128 * m2, 1024, fb);
            tma_load_2d(st + 16384, &tm_yt, 128 * m2, ocol, fb);
            tma_load_2d(st + 24576, &tm_yt, 128 * m2 + 64, ocol, fb);
          }
          if (++slot == NST) { slot = 0; par ^= 1; }
        }
        unsigned old = atomicInc(&g_done, NCTA - 1);
        if (old == NCTA - 1) atomicAdd(&g_epoch, 1u);
      }
    } else {
      const int at = tid - 288;
      const unsigned epoch1 = *(volatile unsigned*)&g_epoch + 1u;
      if (wid == 11) {
#pragma unroll 1
        for (int c = lane; c < 88; c += 32) {
          const int ccol = FCH * jc + (c < 44 ? c : c - 44) * 4;
          const bool on = ccol < F_DIM;
          const __nv_bfloat16* wp = (c < 44 ? wgate : wup) + (size_t)(32 * m1) * F_DIM + (on ? ccol : 0);
          float s0 = 0.f, s1 = 0.f, s2 = 0.f, s3 = 0.f;
          uint2 wv[32];
#pragma unroll
          for (int r = 0; r < 32; r++) wv[r] = ldg_nc2(wp + (size_t)r * F_DIM);
#pragma unroll
          for (int r = 0; r < 32; r++) { s0 += bf_lo(wv[r].x); s1 += bf_hi(wv[r].x); s2 += bf_lo(wv[r].y); s3 += bf_hi(wv[r].y); }
          *reinterpret_cast<float4*>(g_cspart + (size_t)(jc * 16 + m1) * (2 * FCH) + c * 4) = on ? make_float4(s0, s1, s2, s3) : make_float4(0.f, 0.f, 0.f, 0.f);
        }
        __syncwarp();
        if (lane == 0) red_release(&g_cscnt[jc], 1u);
        for (int i = lane; i < 384; i += 32) sts128(sb + OFF_CS + 16 * i, 0, 0, 0, 0);
        for (int i = lane; i < 60; i += 32) sts128(sb + OFF_G + (i / 15) * G_CH + (i % 15) * 16, 0, 0, 0, 0);
        if (lane == 0) wait_counter(&g_cscnt[jc], 16u * epoch1);
        __syncwarp();
#pragma unroll 1
        for (int c = lane; c < 88; c += 32) {
          float4 s = make_float4(0.f, 0.f, 0.f, 0.f);
          const float4* cp = reinterpret_cast<const float4*>(g_cspart + (size_t)(jc * 16) * (2 * FCH)) + c;
#pragma unroll
          for (int mm = 0; mm < 16; mm++) {
            const float4 t = __ldcg(cp + mm * (2 * FCH / 4));
            s.x += t.x; s.y += t.y; s.z += t.z; s.w += t.w;
          }
          const int n = 4 * (c < 44 ? c : c - 44);
          const uint32_t ta = sb + OFF_CS + (c < 44 ? 0 : 3072) + (n >> 6) * 1024 + (n & 7) * 2;
          const int ck = (n & 63) >> 3;
#pragma unroll
          for (int r = 0; r < 3; r++) {
            const uint32_t lo = pack_bf16(s.x, s.y), hi = pack_bf16(s.z, s.w);
            sts64(ta + r * 128 + ((ck ^ r) << 4), lo, hi);
            s.x -= bf_lo(lo); s.y -= bf_hi(lo); s.z -= bf_lo(hi); s.w -= bf_hi(hi);
          }
        }
        fence_proxy_async_smem();
        bar_arrive<4, 352>();
        bar_sync<5, 288>();
        if (lane == 0) red_release(&g_ycnt[bid >> 4], 1u);
      } else {
        const int tb = bid >> 3, hf = wid - 9;
        const int chp = 64 * (bid & 7) + 32 * hf + 2 * (lane >> 1);
        const uint4 sw = *reinterpret_cast<const uint4*>(shift_k + chp * 4);
        const uint32_t w0 = __byte_perm(sw.x, sw.z, 0x5410), w1 = __byte_perm(sw.x, sw.z, 0x7632);
        const uint32_t w2 = __byte_perm(sw.y, sw.w, 0x5410), w3 = __byte_perm(sw.y, sw.w, 0x7632);
        const size_t base = (size_t)((15 - tb) * D_DIM + chp) * 16;
        mbar_wait(bars + BAR_KV, 0);
#pragma unroll 1
        for (int u = 0; u < 4; u++) {
          uint32_t kk[2][12], rr[2][9];
#pragma unroll
          for (int v = 0; v < 2; v++) {
            const uint32_t ka = sb + OFF_UR + (4 * u + 2 * v + (lane & 1)) * 1024 + hf * 64 + (lane >> 1) * 4;
#pragma unroll
            for (int i = 0; i < 12; i++) kk[v][i] = lds32(ka + i * 128);
#pragma unroll
            for (int i = 0; i < 9; i++) rr[v][i] = lds32(ka + KV_STAGE + (i + 3) * 128);
          }
#pragma unroll
          for (int v = 0; v < 2; v++) {
            const int c8 = 4 * u + 2 * v + (lane & 1);
            uint32_t(&r)[9] = rr[v];
#pragma unroll
            for (int i = 0; i < 9; i++) {
              uint32_t a = bmul2(kk[v][i], w3);
              a = badd2(a, bmul2(kk[v][i + 1], w2));
              a = badd2(a, bmul2(kk[v][i + 2], w1));
              a = badd2(a, bmul2(kk[v][i + 3], w0));
              r[i] = bmul2(a, r[i]);
            }
            uint4* da = g_ura + base + (15 - c8);
            uint4* db = g_urb + base + ((15 - c8) ^ 4);
            da[0] = make_uint4(__byte_perm(r[8], r[7], 0x5410), __byte_perm(r[6], r[5], 0x5410), __byte_perm(r[4], r[3], 0x5410), __byte_perm(r[2], r[1], 0x5410));
            da[16] = make_uint4(__byte_perm(r[8], r[7], 0x7632), __byte_perm(r[6], r[5], 0x7632), __byte_perm(r[4], r[3], 0x7632), __byte_perm(r[2], r[1], 0x7632));
            db[0] = make_uint4(__byte_perm(r[7], r[6], 0x5410), __byte_perm(r[5], r[4], 0x5410), __byte_perm(r[3], r[2], 0x5410), __byte_perm(r[1], r[0], 0x5410));
            db[16] = make_uint4(__byte_perm(r[7], r[6], 0x7632), __byte_perm(r[5], r[4], 0x7632), __byte_perm(r[3], r[2], 0x7632), __byte_perm(r[1], r[0], 0x7632));
          }
        }
        bar_sync<6, 64>();
        sts128(sb + OFF_UR + (at >> 3) * UR_A + 4096 + (at & 7) * 16, 0, 0, 0, 0);
        bar_arrive<4, 352>();
        if (at == 0) {
          red_release(&g_kvcnt[bid & 7], 1u);
          mbar_expect_tx(bars + BAR_CONVK, 12 * 4096);
          for (int c = 0; c < 4; c++) bulk_load(sb + OFF_G + c * G_CH + 240, ssm_k + (size_t)(4 * bid + c) * S_LEN, 4096, bars + BAR_CONVK);
          wait_counter(&g_kvcnt[bid >> 4], 16u * epoch1);
          fence_proxy_async();
          for (int c = 0; c < 4; c++) {
            tma_load_3d(sb + OFF_UR + c * UR_CH, &tm_ura, 0, 4 * bid + c, 0, bars + BAR_CONVK);
            tma_load_3d(sb + OFF_UR + c * UR_CH + UR_A, &tm_urb, 0, 4 * bid + c, 0, bars + BAR_CONVK);
          }
        }
        __syncwarp();
        const int g = wid - 9;
        const uint32_t st = sb + OFF_X + g * HSTG;
        if (g == 0) bar_sync<2, 160>(); else bar_sync<3, 160>();
        if (lane == 0) {
          tma_store_2d(&tm_hst64, st, FCH * jc, 128 * m1 + 64 * g);
          asm volatile("cp.async.bulk.commit_group;" ::: "memory");
        }
        __syncwarp();
        if (g == 0) bar_sync<7, 160>(); else bar_sync<8, 160>();
        if (lane == 0) {
          tma_store_2d(&tm_hst64, st + 8192, FCH * jc + 64, 128 * m1 + 64 * g);
          tma_store_2d(&tm_hst48, st + 16384, FCH * jc + 128, 128 * m1 + 64 * g);
          asm volatile("cp.async.bulk.commit_group;" ::: "memory");
          asm volatile("cp.async.bulk.wait_group 1;" ::: "memory");
          red_relaxed(&g_hcnt[(m1 * 8 + jc) * 2], 1u);
          asm volatile("cp.async.bulk.wait_group.read 0;" ::: "memory");
          mbar_arrive(bars + BAR_STG);
          asm volatile("cp.async.bulk.wait_group 0;" ::: "memory");
          red_relaxed(&g_hcnt[(m1 * 8 + jc) * 2 + 1], 1u);
        }
        __syncwarp();
      }
    }
  } else {
    asm volatile("setmaxnreg.inc.sync.aligned.u32 208;");
    const int g = wid >> 2, w4 = wid & 3, p = lane >> 2, q = lane & 3;
    const int row0 = 64 * g + 16 * w4 + p;
    if (tid < 160) {
      const int r = tid % BK1;
      sts128(sb + (tid / BK1) * WST + 2 * WATOM + r * 128 + ((6 ^ (r & 7)) << 4), 0x3F803F80u, 0x3F803F80u, 0x3F803F80u, 0x3F803F80u);
      fence_proxy_async_smem();
    }
    bar_sync<1, 256>();
    cluster_wait();
    {
      float accg[92], accu[88];
#pragma unroll
      for (int i = 0; i < 88; i++) { accg[i] = 0.f; accu[i] = 0.f; }
      accg[88] = accg[89] = accg[90] = accg[91] = 0.f;
      const uint32_t peer_ew = mapa(bars + BAR_EW, rank ^ 1);
      int slot = 0, xs = 0;
      uint32_t par = 0, xpar = 0;
#pragma unroll 1
      for (int it = 0; it < G1_STAGES; it++) {
        const uint32_t st = sb + slot * WST;
        const int xi = it % XPER;
        const uint32_t xa = sb + OFF_X + xs * XST + g * 8192 + xi * (2 * BK1);
        if (xi == 0) mbar_wait(bars + BAR_FX + 8 * xs, xpar);
        mbar_wait(bars + BAR_FW + 8 * slot, par);
        wg_fence();
#pragma unroll
        for (int kk = 0; kk < BK1 / 16; kk++) {
          wgmma_ss_n184(accg, make_desc(xa + 32 * kk, 16, 1024), make_desc(st + 2048 * kk, WATOM, 1024));
          wgmma_ss_n176(accu, make_desc(xa + 32 * kk, 16, 1024), make_desc(st + 3 * WATOM + 2048 * kk, WATOM, 1024));
        }
        wg_commit();
        if (it >= G1_DEPTH) {
          wg_wait<G1_DEPTH>();
          if ((tid & 127) == 0) {
            const int rs = it - G1_DEPTH;
            if (rs < G1_STAGES - NW) {
              mbar_arrive(bars + BAR_EW + 8 * (rs % NW));
              mbar_arrive_remote(peer_ew + 8 * (rs % NW));
            }
            if (rs % XPER == XPER - 1) mbar_arrive(bars + BAR_EX + 8 * ((rs / XPER) % 3));
          }
        }
        if (++slot == NW) { slot = 0; par ^= 1; }
        if (xi == XPER - 1) { if (++xs == 3) { xs = 0; xpar ^= 1; } }
      }
      wg_wait<0>();
#pragma unroll
      for (int i = 0; i < 88; i++) { asm volatile("" : "+f"(accg[i])::"memory"); asm volatile("" : "+f"(accu[i])::"memory"); }
      asm volatile("" : "+f"(accg[88]), "+f"(accg[89]), "+f"(accg[90]), "+f"(accg[91])::"memory");
      if ((tid & 127) == 0) mbar_arrive(bars + BAR_G1);
      bar_sync<4, 352>();
      const uint32_t stg = sb + OFF_X + g * HSTG;
      const int srow = 16 * w4 + (lane & 7) + 8 * ((lane >> 3) & 1);
      {
        const uint32_t n0 = pack_bf16(-accg[88] * (1.f / D_DIM), -accg[88] * (1.f / D_DIM));
        const uint32_t n1 = pack_bf16(-accg[90] * (1.f / D_DIM), -accg[90] * (1.f / D_DIM));
        const uint32_t ap = stg + 22528 + (16 * w4 + p) * 16;
        if (q < 2) sts128(ap + q * 128, q ? n1 : n0, (q ? n1 : n0) & 0xffffu, 0u, 0u);
        else sts128(ap + 1024 + (q - 2) * 128, 0u, 0u, 0u, 0u);
        fence_proxy_async_smem();
        if (g == 0) bar_sync<9, 128>(); else bar_sync<10, 128>();
        const uint64_t da = (uint64_t)(((stg + 22528) & 0x3FFFF) >> 4) | ((uint64_t)(1024 >> 4) << 16) | ((uint64_t)(128 >> 4) << 32);
        wg_fence();
        wgmma_ss_n184(accg, da, make_desc(sb + OFF_CS, 1024, 0));
        wgmma_ss_n176(accu, da, make_desc(sb + OFF_CS + 3072, 1024, 0));
        wg_commit();
        wg_wait<0>();
#pragma unroll
        for (int i = 0; i < 88; i++) { asm volatile("" : "+f"(accg[i])::"memory"); asm volatile("" : "+f"(accu[i])::"memory"); }
      }
#pragma unroll
      for (int i = 0; i < 11; i++) {
        uint32_t h[4];
#pragma unroll
        for (int b = 0; b < 2; b++) {
          const int r = 8 * i + 4 * b;
          h[2 * b] = bmul2(pack_bf16(accg[r], accg[r + 1]), pack_bf16(accu[r], accu[r + 1]));
          h[2 * b + 1] = bmul2(pack_bf16(accg[r + 2], accg[r + 3]), pack_bf16(accu[r + 2], accu[r + 3]));
        }
        const int blkc = 2 * i + (lane >> 4);
        uint32_t addr;
        if (i < 8) addr = stg + (i >> 2) * 8192 + srow * 128 + (((blkc & 7) ^ (srow & 7)) << 4);
        else addr = stg + 16384 + srow * 96 + ((blkc - 16) << 4);
        stsm_x4(addr, h[0], h[1], h[2], h[3]);
        if (i == 3) {
          fence_proxy_async_smem();
          if (g == 0) bar_arrive<2, 160>(); else bar_arrive<3, 160>();
        }
      }
      fence_proxy_async_smem();
      if (g == 0) bar_arrive<7, 160>(); else bar_arrive<8, 160>();
    }
    float acc[64];
#pragma unroll
    for (int i = 0; i < 64; i++) acc[i] = 0.f;
    int slot = 0, s2 = 0;
    uint32_t par = 0;
    auto gemm2_stages = [&](int send) {
#pragma unroll 1
      for (; s2 < send; s2++) {
        const uint32_t st = sb + slot * STAGE;
        mbar_wait(bars + BAR_F2 + 8 * slot, par);
        if (s2 < 4 || !(s2 & 1)) {
          wg_fence();
#pragma unroll
          for (int kk = 0; kk < 4; kk++)
            wgmma_ss_n128(acc, make_desc(st + g * 8192 + kk * 32, 16, 1024), make_desc(st + 16384 + kk * 2048, 8192, 1024));
          wg_commit();
        } else {
          wg_fence();
#pragma unroll
          for (int kk = 0; kk < 3; kk++)
            wgmma_ss_n128(acc, make_desc(st + g * 8192 + kk * 32, 16, 1024), make_desc(st + 16384 + kk * 2048, 8192, 1024));
          wg_commit();
        }
        wg_wait<0>();
        if ((tid & 127) == 0) mbar_arrive(bars + BAR_E2 + 8 * slot);
        if (++slot == NST) { slot = 0; par ^= 1; }
      }
    };
    {
      const int ch = wid >> 1, part = wid & 1;
      const uint32_t urb = sb + OFF_UR + ch * UR_CH;
      const uint32_t gaddr = sb + OFF_G + ch * G_CH + 16 * ((lane & 7) + 8 * ((lane >> 3) & 1) + (lane >> 4));
      const uint32_t faddr = (p & 1) ? urb + 2 * (1927 - p + 2 * q) : urb + UR_A + 2 * (1926 - p + 2 * q);
      const uint32_t fxor = (p & 1) ? 0u : 64u;
      float cacc[11][4];
#pragma unroll
      for (int i = 0; i < 11; i++) cacc[i][0] = cacc[i][1] = cacc[i][2] = cacc[i][3] = 0.f;
      mbar_wait(bars + BAR_CONVK, 0);
#pragma unroll 1
      for (int r2 = 0; r2 < 8; r2 += 2) {
        if (r2 == G2_RHO0) gemm2_stages(G2_MID);
        const uint32_t fa = faddr + 32 * r2, ga = gaddr + 32 * r2;
        if (part) {
          conv_rho<1>(cacc, ga, fa ^ fxor, (fa + 16) ^ fxor);
          conv_rho<1>(cacc, ga + 32, (fa + 32) ^ fxor, (fa + 48) ^ fxor);
        } else {
          conv_rho<0>(cacc, ga, fa ^ fxor, (fa + 16) ^ fxor);
          conv_rho<0>(cacc, ga + 32, (fa + 32) ^ fxor, (fa + 48) ^ fxor);
        }
      }
      const uint32_t kvaddr = urb + 2 * (2046 - 8 * p - 2 * q);
      const unsigned short dv = reinterpret_cast<const unsigned short*>(ssm_D)[4 * bid + ch];
      const uint32_t dd = (uint32_t)dv * 0x10001u;
      __nv_bfloat16* yrow = g_yt + (size_t)(4 * bid + ch) * S_LEN + 8 * p + 2 * q;
      if (part) conv_store<1>(cacc, kvaddr, dd, yrow);
      else conv_store<0>(cacc, kvaddr, dd, yrow);
      bar_arrive<5, 288>();
      if (lane == 0) mbar_arrive_remote(mapa(bars + BAR_PEER, rank ^ 1));
    }
    gemm2_stages(G2_STAGES);
    mbar_wait(bars + BAR_PEER, 0);
#pragma unroll
    for (int i = 0; i < 64; i++) asm volatile("" : "+f"(acc[i])::"memory");
    float o[32];
    {
      const uint32_t rbuf = mapa(sb + OFF_UR + tid * 16, rank ^ 1), rbar = mapa(bars + BAR_XCH, rank ^ 1);
      if (kh == 0) {
#pragma unroll
        for (int v = 0; v < 8; v++) st_async_v4(rbuf + v * 4096, acc[32 + 4 * v], acc[33 + 4 * v], acc[34 + 4 * v], acc[35 + 4 * v], rbar);
#pragma unroll
        for (int i = 0; i < 32; i++) o[i] = acc[i];
      } else {
#pragma unroll
        for (int v = 0; v < 8; v++) st_async_v4(rbuf + v * 4096, acc[4 * v], acc[1 + 4 * v], acc[2 + 4 * v], acc[3 + 4 * v], rbar);
#pragma unroll
        for (int i = 0; i < 32; i++) o[i] = acc[32 + i];
      }
    }
    {
      const uint32_t st = sb + slot * STAGE;
      mbar_wait(bars + BAR_F2 + 8 * slot, par);
      const float2 st0 = lds64f(sb + OFF_ST + 8 * row0), st1 = lds64f(sb + OFF_ST + 8 * row0 + 64);
      const uint32_t mean0 = pack_bf16(st0.x, st0.x), mean1 = pack_bf16(st1.x, st1.x);
      uint32_t xv[16], sv[16];
      const int dl = (lane & 7) + 8 * (lane >> 4), tc = 2 * w4 + ((lane >> 3) & 1);
      const int xrow = 64 * g + 16 * w4 + (lane & 7) + 8 * ((lane >> 3) & 1);
#pragma unroll
      for (int v2 = 0; v2 < 4; v2++) {
        uint32_t y[4];
        const int d = 16 * v2 + dl;
        ldsm_x4_t(st + 16384 + g * 8192 + d * 128 + ((tc ^ (d & 7)) << 4), y[0], y[1], y[2], y[3]);
        ldsm_x4(st + xrow * 128 + (((2 * v2 + (lane >> 4)) ^ (xrow & 7)) << 4), xv[4 * v2], xv[4 * v2 + 1], xv[4 * v2 + 2], xv[4 * v2 + 3]);
#pragma unroll
        for (int e = 0; e < 4; e++) {
          const uint32_t xc = bsub2(xv[4 * v2 + e], (e & 1) ? mean1 : mean0);
          const float rs = (e & 1) ? st1.y : st0.y;
          sv[4 * v2 + e] = bmul2(pack_bf16(bf_lo(xc) * rs, bf_hi(xc) * rs), y[e]);
        }
      }
      mbar_wait(bars + BAR_XCH, 0);
#pragma unroll
      for (int v2 = 0; v2 < 4; v2++) {
        uint32_t res[4];
#pragma unroll
        for (int b = 0; b < 2; b++) {
          const int v = 2 * v2 + b;
          const float4 r = lds128f(sb + OFF_UR + tid * 16 + v * 4096);
#pragma unroll
          for (int hh = 0; hh < 2; hh++) {
            const float r2 = hh ? st1.y * st1.y : st0.y * st0.y;
            const uint32_t ob = pack_bf16((o[4 * v + 2 * hh] + (hh ? r.z : r.x)) * r2, (o[4 * v + 2 * hh + 1] + (hh ? r.w : r.y)) * r2);
            const float h0 = 0.5f * bf_lo(ob), h1 = 0.5f * bf_hi(ob);
            const uint32_t gs = pack_bf16(fmaf(h0, tanh_fast(h0), h0), fmaf(h1, tanh_fast(h1), h1));
            res[2 * b + hh] = badd2(xv[4 * v2 + 2 * b + hh], bmul2(sv[4 * v2 + 2 * b + hh], gs));
          }
        }
        stsm_x4(st + xrow * 128 + (((2 * v2 + (lane >> 4)) ^ (xrow & 7)) << 4), res[0], res[1], res[2], res[3]);
      }
      fence_proxy_async_smem();
      if (g == 0) bar_sync<2, 128>(); else bar_sync<3, 128>();
      if ((tid & 127) == 0) {
        tma_store_2d(&tm_out, st + g * 8192, ocol, 128 * m2 + 64 * g);
        asm volatile("cp.async.bulk.commit_group;" ::: "memory");
        asm volatile("cp.async.bulk.wait_group.read 0;" ::: "memory");
      }
    }
  }
}

typedef CUresult (*EncodeTiledFn)(CUtensorMap*, CUtensorMapDataType, cuuint32_t, void*, const cuuint64_t*, const cuuint64_t*,
                                  const cuuint32_t*, const cuuint32_t*, CUtensorMapInterleave, CUtensorMapSwizzle,
                                  CUtensorMapL2promotion, CUtensorMapFloatOOBfill);

static void make_map(EncodeTiledFn enc, CUtensorMap* m, const void* ptr, uint64_t cols, uint64_t rows, uint32_t bcols, uint32_t brows,
                     CUtensorMapSwizzle swz) {
  cuuint64_t dims[2] = {cols, rows};
  cuuint64_t strides[1] = {cols * 2};
  cuuint32_t box[2] = {bcols, brows};
  cuuint32_t es[2] = {1, 1};
  enc(m, CU_TENSOR_MAP_DATA_TYPE_BFLOAT16, 2, const_cast<void*>(ptr), dims, strides, box, es, CU_TENSOR_MAP_INTERLEAVE_NONE, swz,
      CU_TENSOR_MAP_L2_PROMOTION_L2_128B, CU_TENSOR_MAP_FLOAT_OOB_FILL_NONE);
}

static void make_map_2atoms(EncodeTiledFn enc, CUtensorMap* m, const void* ptr, uint64_t cols, uint64_t rows, uint32_t brows) {
  cuuint64_t dims[3] = {cols - 64, rows, 2};
  cuuint64_t strides[2] = {cols * 2, 128};
  cuuint32_t box[3] = {64, brows, 2};
  cuuint32_t es[3] = {1, 1, 1};
  enc(m, CU_TENSOR_MAP_DATA_TYPE_BFLOAT16, 3, const_cast<void*>(ptr), dims, strides, box, es, CU_TENSOR_MAP_INTERLEAVE_NONE,
      CU_TENSOR_MAP_SWIZZLE_128B, CU_TENSOR_MAP_L2_PROMOTION_L2_128B, CU_TENSOR_MAP_FLOAT_OOB_FILL_NONE);
}

extern "C" void kernel_launch(void* const* d_in, const int* in_sizes, int n_in, void* d_out, int out_size) {
  (void)in_sizes; (void)n_in; (void)out_size;
  const __nv_bfloat16* x = (const __nv_bfloat16*)d_in[0];
  const __nv_bfloat16* k = (const __nv_bfloat16*)d_in[1];
  const __nv_bfloat16* v = (const __nv_bfloat16*)d_in[2];
  const __nv_bfloat16* shift_k = (const __nv_bfloat16*)d_in[3];
  const __nv_bfloat16* ssm_k = (const __nv_bfloat16*)d_in[4];
  const __nv_bfloat16* ssm_D = (const __nv_bfloat16*)d_in[5];
  const __nv_bfloat16* wg = (const __nv_bfloat16*)d_in[7];
  const __nv_bfloat16* wu = (const __nv_bfloat16*)d_in[8];
  const __nv_bfloat16* wd = (const __nv_bfloat16*)d_in[9];

  static EncodeTiledFn enc = nullptr;
  static void* ph = nullptr;
  static void* pyt = nullptr;
  static void* pura = nullptr;
  static void* purb = nullptr;
  if (!enc) {
    void* fn = nullptr;
    cudaDriverEntryPointQueryResult qr;
    cudaGetDriverEntryPoint("cuTensorMapEncodeTiled", &fn, cudaEnableDefault, &qr);
    enc = (EncodeTiledFn)fn;
    cudaGetSymbolAddress(&ph, g_h);
    cudaGetSymbolAddress(&pyt, g_yt);
    cudaGetSymbolAddress(&pura, g_ura);
    cudaGetSymbolAddress(&purb, g_urb);
    cudaFuncSetAttribute(h3_glu_kernel, cudaFuncAttributeMaxDynamicSharedMemorySize, SMEM_BYTES);
  }
  CUtensorMap tm_x, tm_out, tm_wg, tm_wu, tm_wg48, tm_wu48, tm_wd, tm_hld, tm_wd48, tm_hld48, tm_hst64, tm_hst48, tm_yt, tm_k, tm_v, tm_ura, tm_urb;
  make_map(enc, &tm_x, x, D_DIM, S_LEN, 64, 128, CU_TENSOR_MAP_SWIZZLE_128B);
  make_map(enc, &tm_out, d_out, D_DIM, S_LEN, 64, 64, CU_TENSOR_MAP_SWIZZLE_128B);
  make_map_2atoms(enc, &tm_wg, wg, F_DIM, D_DIM, BK1);
  make_map_2atoms(enc, &tm_wu, wu, F_DIM, D_DIM, BK1);
  make_map(enc, &tm_wg48, wg, F_DIM, D_DIM, 48, BK1, CU_TENSOR_MAP_SWIZZLE_128B);
  make_map(enc, &tm_wu48, wu, F_DIM, D_DIM, 48, BK1, CU_TENSOR_MAP_SWIZZLE_128B);
  make_map_2atoms(enc, &tm_wd, wd, D_DIM, F_DIM, 64);
  make_map(enc, &tm_hld, ph, F_DIM, S_LEN, 64, 128, CU_TENSOR_MAP_SWIZZLE_128B);
  make_map(enc, &tm_wd48, wd, D_DIM, F_DIM, 64, 48, CU_TENSOR_MAP_SWIZZLE_128B);
  make_map(enc, &tm_hld48, ph, F_DIM, S_LEN, 48, 128, CU_TENSOR_MAP_SWIZZLE_128B);
  make_map(enc, &tm_hst64, ph, F_DIM, S_LEN, 64, 64, CU_TENSOR_MAP_SWIZZLE_128B);
  make_map(enc, &tm_hst48, ph, F_DIM, S_LEN, 48, 64, CU_TENSOR_MAP_SWIZZLE_NONE);
  make_map(enc, &tm_yt, pyt, S_LEN, D_DIM, 64, 64, CU_TENSOR_MAP_SWIZZLE_128B);
  make_map(enc, &tm_k, k, D_DIM, S_LEN, 64, 132, CU_TENSOR_MAP_SWIZZLE_NONE);
  make_map(enc, &tm_v, v, D_DIM, S_LEN, 64, 132, CU_TENSOR_MAP_SWIZZLE_NONE);
  for (int c = 0; c < 2; c++) {
    cuuint64_t dims[3] = {128, D_DIM, 16};
    cuuint64_t strides[2] = {256, (cuuint64_t)D_DIM * 256};
    cuuint32_t box[3] = {128, 1, 16};
    cuuint32_t es[3] = {1, 1, 1};
    enc(c ? &tm_urb : &tm_ura, CU_TENSOR_MAP_DATA_TYPE_BFLOAT16, 3, c ? purb : pura, dims, strides, box, es, CU_TENSOR_MAP_INTERLEAVE_NONE,
        CU_TENSOR_MAP_SWIZZLE_NONE, CU_TENSOR_MAP_L2_PROMOTION_L2_128B, CU_TENSOR_MAP_FLOAT_OOB_FILL_NONE);
  }
  h3_glu_kernel<<<NCTA + 4, NTHREADS, SMEM_BYTES, cudaStreamPerThread>>>(tm_x, tm_out, tm_wg, tm_wu, tm_wg48, tm_wu48, tm_wd, tm_hld, tm_wd48, tm_hld48, tm_hst64, tm_hst48, tm_yt, tm_k, tm_v, tm_ura, tm_urb,
                                                                    x, wg, wu, wd, shift_k, ssm_k, ssm_D);
}
```
